```python
import torch

def _softmax(x, axis=-1):
    return torch.softmax(x, dim=axis)

def _gelu(x):
    return torch.nn.functional.gelu(x, approximate='tanh')

def _silu(x):
    return torch.nn.functional.silu(x)

def _sigmoid(x):
    return torch.sigmoid(x)

def _layernorm(x, axis=-1, eps=1e-05):
    m = x.mean(dim=axis, keepdim=True)
    v = x.var(dim=axis, keepdim=True, unbiased=False)
    return (x - m) / torch.sqrt(v + eps)

def _scatter_add(tgt, idx, src, axis=0):
    return tgt.clone().index_add_(axis, idx, src)

def _segment_sum(src, seg, n):
    out = torch.zeros((n,) + src.shape[1:], dtype=src.dtype)
    return out.index_add_(0, seg, src)

def _pad(x, pw):
    flat = tuple((v for pair in reversed(pw) for v in pair))
    return torch.nn.functional.pad(x, flat)
kernel_name = 'adaLN_cond__spectral_gfnet__glu_gated_swiglu__prompt'

def setup_inputs():

    _w = lambda a: (lambda t: t.to(torch.bfloat16) if t.is_floating_point() else t)(torch.as_tensor(a))

    def _A_setup():
        B, S, D = (1, 2048, 512)
        Df = D // 2 + 1
        return {'x': _w((lambda *s: torch.randn(*s, dtype=torch.bfloat16) * 0.05)(B, S, D)), 'w_r': _w((lambda *s: torch.randn(*s, dtype=torch.bfloat16) * 3.2)(S, Df) * 0.02), 'w_i': _w((lambda *s: torch.randn(*s, dtype=torch.bfloat16) * 3.2)(S, Df) * 0.02)}
    _A_in = _A_setup()

    def _B_setup():
        B, S, D, F = (1, 2048, 512, 1376)
        return {'x': _w((lambda *s: torch.randn(*s, dtype=torch.bfloat16) * 0.05)(B, S, D)), 'w1': _w((lambda *s: torch.randn(*s, dtype=torch.bfloat16) * 0.4)(D, F) * (2.0 / D) ** 0.5), 'w3': _w((lambda *s: torch.randn(*s, dtype=torch.bfloat16) * 0.4)(D, F) * (2.0 / D) ** 0.5), 'w2': _w((lambda *s: torch.randn(*s, dtype=torch.bfloat16) * 0.4)(F, D) * (2.0 / F) ** 0.5)}
    _B_in = _B_setup()
    return {'A_x': _A_in['x'], 'A_w_r': _A_in['w_r'], 'A_w_i': _A_in['w_i'], 'B_x': _B_in['x'], 'B_w1': _B_in['w1'], 'B_w3': _B_in['w3'], 'B_w2': _B_in['w2'], 'c': _w((lambda *s: torch.randn(*s, dtype=torch.bfloat16) * 0.1)(1, 512) * 8.0), 'w_mod': _w((lambda *s: torch.randn(*s, dtype=torch.bfloat16) * 0.1)(512, 6 * 512) * 512 ** (-0.5) * 8.0)}

def reference(A_x, A_w_r, A_w_i, B_x, B_w1, B_w3, B_w2, c, w_mod):

    def _A_ref(x, w_r, w_i):
        B, S, D = x.shape
        X = (lambda x, axes=(-2, -1): torch.fft.rfft2(x.float(), dim=axes))(x, axes=(-2, -1))
        W = w_r + 1j * w_i
        X = X * W
        y = (lambda x, s, axes=(-2, -1): torch.fft.irfft2(x, s=s, dim=axes).to(torch.bfloat16))(X, (S, D), axes=(-2, -1))
        return y

    def _B_ref(x, w1, w3, w2):
        gate = torch.einsum('bsd,df->bsf', x, w1)
        up = torch.einsum('bsd,df->bsf', x, w3)
        h = _silu(gate) * up
        out = torch.einsum('bsf,fd->bsd', h, w2)
        return out
    x = A_x
    mod = (_silu(c) @ w_mod).reshape(c.shape[0], 6, 1, -1)
    sa, ca, ga, sb, cb, gb = (mod[:, 0].clone(), mod[:, 1].clone(), mod[:, 2].clone(), mod[:, 3].clone(), mod[:, 4].clone(), mod[:, 5].clone())
    h = _layernorm(x, axis=-1) * (1 + ca) + sa
    x = x + ga * _A_ref(h, A_w_r, A_w_i)
    h = _layernorm(x, axis=-1) * (1 + cb) + sb
    x = x + gb * _B_ref(h, B_w1, B_w3, B_w2)
    return x
```

```cpp
#include <cuda_runtime.h>
#include <cuda_bf16.h>
#include <cuda.h>
#include <stdint.h>

__device__ __forceinline__ void wgmma_rs_n128_tb1(float (&d)[64], uint32_t a0, uint32_t a1, uint32_t a2, uint32_t a3, uint64_t db, int scale_d) {
  asm volatile("{\n.reg .pred p;\nsetp.ne.b32 p, %69, 0;\n"
    "wgmma.mma_async.sync.aligned.m64n128k16.f32.bf16.bf16 {%0, %1, %2, %3, %4, %5, %6, %7, %8, %9, %10, %11, %12, %13, %14, %15, %16, %17, %18, %19, %20, %21, %22, %23, %24, %25, %26, %27, %28, %29, %30, %31, %32, %33, %34, %35, %36, %37, %38, %39, %40, %41, %42, %43, %44, %45, %46, %47, %48, %49, %50, %51, %52, %53, %54, %55, %56, %57, %58, %59, %60, %61, %62, %63}, {%64, %65, %66, %67}, %68, p, 1, 1, 1;\n}\n"
    : "+f"(d[0]), "+f"(d[1]), "+f"(d[2]), "+f"(d[3]), "+f"(d[4]), "+f"(d[5]), "+f"(d[6]), "+f"(d[7]), "+f"(d[8]), "+f"(d[9]), "+f"(d[10]), "+f"(d[11]), "+f"(d[12]), "+f"(d[13]), "+f"(d[14]), "+f"(d[15]), "+f"(d[16]), "+f"(d[17]), "+f"(d[18]), "+f"(d[19]), "+f"(d[20]), "+f"(d[21]), "+f"(d[22]), "+f"(d[23]), "+f"(d[24]), "+f"(d[25]), "+f"(d[26]), "+f"(d[27]), "+f"(d[28]), "+f"(d[29]), "+f"(d[30]), "+f"(d[31]), "+f"(d[32]), "+f"(d[33]), "+f"(d[34]), "+f"(d[35]), "+f"(d[36]), "+f"(d[37]), "+f"(d[38]), "+f"(d[39]), "+f"(d[40]), "+f"(d[41]), "+f"(d[42]), "+f"(d[43]), "+f"(d[44]), "+f"(d[45]), "+f"(d[46]), "+f"(d[47]), "+f"(d[48]), "+f"(d[49]), "+f"(d[50]), "+f"(d[51]), "+f"(d[52]), "+f"(d[53]), "+f"(d[54]), "+f"(d[55]), "+f"(d[56]), "+f"(d[57]), "+f"(d[58]), "+f"(d[59]), "+f"(d[60]), "+f"(d[61]), "+f"(d[62]), "+f"(d[63])
    : "r"(a0), "r"(a1), "r"(a2), "r"(a3), "l"(db), "r"(scale_d));
}
__device__ __forceinline__ void wgmma_rs_n64_tb1(float (&d)[32], uint32_t a0, uint32_t a1, uint32_t a2, uint32_t a3, uint64_t db, int scale_d) {
  asm volatile("{\n.reg .pred p;\nsetp.ne.b32 p, %37, 0;\n"
    "wgmma.mma_async.sync.aligned.m64n64k16.f32.bf16.bf16 {%0, %1, %2, %3, %4, %5, %6, %7, %8, %9, %10, %11, %12, %13, %14, %15, %16, %17, %18, %19, %20, %21, %22, %23, %24, %25, %26, %27, %28, %29, %30, %31}, {%32, %33, %34, %35}, %36, p, 1, 1, 1;\n}\n"
    : "+f"(d[0]), "+f"(d[1]), "+f"(d[2]), "+f"(d[3]), "+f"(d[4]), "+f"(d[5]), "+f"(d[6]), "+f"(d[7]), "+f"(d[8]), "+f"(d[9]), "+f"(d[10]), "+f"(d[11]), "+f"(d[12]), "+f"(d[13]), "+f"(d[14]), "+f"(d[15]), "+f"(d[16]), "+f"(d[17]), "+f"(d[18]), "+f"(d[19]), "+f"(d[20]), "+f"(d[21]), "+f"(d[22]), "+f"(d[23]), "+f"(d[24]), "+f"(d[25]), "+f"(d[26]), "+f"(d[27]), "+f"(d[28]), "+f"(d[29]), "+f"(d[30]), "+f"(d[31])
    : "r"(a0), "r"(a1), "r"(a2), "r"(a3), "l"(db), "r"(scale_d));
}
__device__ __forceinline__ void wgmma_rs_n48_tb1(float (&d)[24], uint32_t a0, uint32_t a1, uint32_t a2, uint32_t a3, uint64_t db, int scale_d) {
  asm volatile("{\n.reg .pred p;\nsetp.ne.b32 p, %29, 0;\n"
    "wgmma.mma_async.sync.aligned.m64n48k16.f32.bf16.bf16 {%0, %1, %2, %3, %4, %5, %6, %7, %8, %9, %10, %11, %12, %13, %14, %15, %16, %17, %18, %19, %20, %21, %22, %23}, {%24, %25, %26, %27}, %28, p, 1, 1, 1;\n}\n"
    : "+f"(d[0]), "+f"(d[1]), "+f"(d[2]), "+f"(d[3]), "+f"(d[4]), "+f"(d[5]), "+f"(d[6]), "+f"(d[7]), "+f"(d[8]), "+f"(d[9]), "+f"(d[10]), "+f"(d[11]), "+f"(d[12]), "+f"(d[13]), "+f"(d[14]), "+f"(d[15]), "+f"(d[16]), "+f"(d[17]), "+f"(d[18]), "+f"(d[19]), "+f"(d[20]), "+f"(d[21]), "+f"(d[22]), "+f"(d[23])
    : "r"(a0), "r"(a1), "r"(a2), "r"(a3), "l"(db), "r"(scale_d));
}
__device__ __forceinline__ void wgmma_rs_n32_tb1(float (&d)[16], uint32_t a0, uint32_t a1, uint32_t a2, uint32_t a3, uint64_t db, int scale_d) {
  asm volatile("{\n.reg .pred p;\nsetp.ne.b32 p, %21, 0;\n"
    "wgmma.mma_async.sync.aligned.m64n32k16.f32.bf16.bf16 {%0, %1, %2, %3, %4, %5, %6, %7, %8, %9, %10, %11, %12, %13, %14, %15}, {%16, %17, %18, %19}, %20, p, 1, 1, 1;\n}\n"
    : "+f"(d[0]), "+f"(d[1]), "+f"(d[2]), "+f"(d[3]), "+f"(d[4]), "+f"(d[5]), "+f"(d[6]), "+f"(d[7]), "+f"(d[8]), "+f"(d[9]), "+f"(d[10]), "+f"(d[11]), "+f"(d[12]), "+f"(d[13]), "+f"(d[14]), "+f"(d[15])
    : "r"(a0), "r"(a1), "r"(a2), "r"(a3), "l"(db), "r"(scale_d));
}
__device__ __forceinline__ void wgmma_rs_n40_tb1(float (&d)[20], uint32_t a0, uint32_t a1, uint32_t a2, uint32_t a3, uint64_t db, int scale_d) {
  asm volatile("{\n.reg .pred p;\nsetp.ne.b32 p, %25, 0;\n"
    "wgmma.mma_async.sync.aligned.m64n40k16.f32.bf16.bf16 {%0, %1, %2, %3, %4, %5, %6, %7, %8, %9, %10, %11, %12, %13, %14, %15, %16, %17, %18, %19}, {%20, %21, %22, %23}, %24, p, 1, 1, 1;\n}\n"
    : "+f"(d[0]), "+f"(d[1]), "+f"(d[2]), "+f"(d[3]), "+f"(d[4]), "+f"(d[5]), "+f"(d[6]), "+f"(d[7]), "+f"(d[8]), "+f"(d[9]), "+f"(d[10]), "+f"(d[11]), "+f"(d[12]), "+f"(d[13]), "+f"(d[14]), "+f"(d[15]), "+f"(d[16]), "+f"(d[17]), "+f"(d[18]), "+f"(d[19])
    : "r"(a0), "r"(a1), "r"(a2), "r"(a3), "l"(db), "r"(scale_d));
}
__device__ __forceinline__ void wgmma_rs_n64_tb0(float (&d)[32], uint32_t a0, uint32_t a1, uint32_t a2, uint32_t a3, uint64_t db, int scale_d) {
  asm volatile("{\n.reg .pred p;\nsetp.ne.b32 p, %37, 0;\n"
    "wgmma.mma_async.sync.aligned.m64n64k16.f32.bf16.bf16 {%0, %1, %2, %3, %4, %5, %6, %7, %8, %9, %10, %11, %12, %13, %14, %15, %16, %17, %18, %19, %20, %21, %22, %23, %24, %25, %26, %27, %28, %29, %30, %31}, {%32, %33, %34, %35}, %36, p, 1, 1, 0;\n}\n"
    : "+f"(d[0]), "+f"(d[1]), "+f"(d[2]), "+f"(d[3]), "+f"(d[4]), "+f"(d[5]), "+f"(d[6]), "+f"(d[7]), "+f"(d[8]), "+f"(d[9]), "+f"(d[10]), "+f"(d[11]), "+f"(d[12]), "+f"(d[13]), "+f"(d[14]), "+f"(d[15]), "+f"(d[16]), "+f"(d[17]), "+f"(d[18]), "+f"(d[19]), "+f"(d[20]), "+f"(d[21]), "+f"(d[22]), "+f"(d[23]), "+f"(d[24]), "+f"(d[25]), "+f"(d[26]), "+f"(d[27]), "+f"(d[28]), "+f"(d[29]), "+f"(d[30]), "+f"(d[31])
    : "r"(a0), "r"(a1), "r"(a2), "r"(a3), "l"(db), "r"(scale_d));
}

namespace {

constexpr int NCTA = 129;
constexpr int TS = 2080;
constexpr int XS = 1040;
constexpr int NSLOT = 13;
constexpr int SLOT = 16384;
constexpr int NSTAGE = 36;
constexpr int NEARLY = 10;
constexpr int OFF_X = NEARLY * SLOT;
constexpr int OFF_Y = OFF_X + 10 * TS;
constexpr int OFF_XRAW = NSLOT * SLOT;
constexpr int OFF_STAT = OFF_XRAW + 16 * XS;
constexpr int OFF_RED = OFF_STAT + 1024;
constexpr int OFF_BAR = OFF_RED + 384;
constexpr int SMEM_BYTES = OFF_BAR + 2 * NSLOT * 8 + 16;
static_assert(OFF_Y + 10 * TS <= NSLOT * SLOT, "scratch overflows ring");
static_assert(SMEM_BYTES <= 232448, "smem");
constexpr int SPIN_LIMIT = 1 << 18;

struct __align__(1024) Scratch {
  uint32_t G[128 * 9 * 512];
  uint32_t Z[128 * 9 * 512];
  uint4 H2[128 * 32 * 32];
  uint4 X1[128 * 32 * 32];
  uint4 H[128 * 88 * 32];
  uint32_t MA[128 * 8];
  uint32_t MB[8 * 4 * 4 * 16];
  uint32_t flagG[2 * 128];
  uint32_t flagZ[2 * 128 + 32];
  uint32_t flagH2[128 * 8];
  uint32_t flagH[3 * 128 * 8];
  uint32_t epoch;
};
__device__ Scratch g_s;

#define STAMP(i)

__device__ __forceinline__ uint32_t s2u(const void* p) { return (uint32_t)__cvta_generic_to_shared(p); }
__device__ __forceinline__ void wg_fence() { asm volatile("wgmma.fence.sync.aligned;" ::: "memory"); }
__device__ __forceinline__ void wg_commit() { asm volatile("wgmma.commit_group.sync.aligned;" ::: "memory"); }
template <int N> __device__ __forceinline__ void wg_wait() { asm volatile("wgmma.wait_group.sync.aligned %0;" ::"n"(N) : "memory"); }
template <int N> __device__ __forceinline__ void pin(float (&d)[N]) {
#pragma unroll
  for (int i = 0; i < N; i++) asm volatile("" : "+f"(d[i])::"memory");
}
__device__ __forceinline__ void fence_async_smem() { asm volatile("fence.proxy.async.shared::cta;" ::: "memory"); }
__device__ __forceinline__ void bar_sync(int id, int n) { asm volatile("bar.sync %0, %1;" ::"r"(id), "r"(n) : "memory"); }
__device__ __forceinline__ void bar_arrive(int id, int n) { asm volatile("bar.arrive %0, %1;" ::"r"(id), "r"(n) : "memory"); }
__device__ __forceinline__ uint64_t mkdesc(uint32_t addr, uint32_t lbo, uint32_t sbo, uint32_t sw) {
  return (uint64_t)((addr & 0x3FFFF) >> 4) | ((uint64_t)(lbo >> 4) << 16) | ((uint64_t)(sbo >> 4) << 32) | ((uint64_t)sw << 62);
}
__device__ __forceinline__ void mbar_init(uint32_t b, int c) { asm volatile("mbarrier.init.shared::cta.b64 [%0], %1;" ::"r"(b), "r"(c) : "memory"); }
__device__ __forceinline__ void mbar_expect(uint32_t b, int bytes) { asm volatile("mbarrier.arrive.expect_tx.shared::cta.b64 _, [%0], %1;" ::"r"(b), "r"(bytes) : "memory"); }
__device__ __forceinline__ void mbar_arrive(uint32_t b) { asm volatile("mbarrier.arrive.shared::cta.b64 _, [%0];" ::"r"(b) : "memory"); }
__device__ __forceinline__ void mbar_wait(uint32_t b, uint32_t ph) {
  uint32_t ok;
  int it = 0;
  do {
    asm volatile("{.reg .pred p; mbarrier.try_wait.parity.shared::cta.b64 p, [%1], %2; selp.u32 %0,1,0,p;}" : "=r"(ok) : "r"(b), "r"(ph) : "memory");
  } while (!ok && ++it < SPIN_LIMIT);
}
__device__ __forceinline__ void tma2d(uint32_t dst, const CUtensorMap* m, int c0, int c1, uint32_t bar) {
  asm volatile("cp.async.bulk.tensor.2d.shared::cluster.global.mbarrier::complete_tx::bytes [%0], [%1, {%3, %4}], [%2];"
               ::"r"(dst), "l"(m), "r"(bar), "r"(c0), "r"(c1) : "memory");
}
__device__ __forceinline__ uint32_t pack2(float lo, float hi) {
  uint32_t r;
  asm("cvt.rn.bf16x2.f32 %0, %1, %2;" : "=r"(r) : "f"(hi), "f"(lo));
  return r;
}
__device__ __forceinline__ float lo2f(uint32_t v) { return __uint_as_float(v << 16); }
__device__ __forceinline__ float hi2f(uint32_t v) { return __uint_as_float(v & 0xFFFF0000u); }
__device__ __forceinline__ float bfround(float v) { return lo2f(pack2(v, 0.f)); }
__device__ __forceinline__ float cosu(int phase) {
  float f = __uint_as_float(((phase + 1024) & 2047) | 0x4B000000) - 8389632.0f;
  return __cosf(f * 0.0030679615757712823f);
}
__device__ __forceinline__ float sinu(int phase) { return cosu(phase - 512); }
__device__ __forceinline__ int idx_of(int sg) {
  int k = 2 * (sg & 15) + (sg >> 6), q = (sg >> 4) & 3;
  int r = (q & 1) ? (k ? 64 - k : 32) : k;
  return r + (q >> 1) * 64;
}
__device__ __forceinline__ int sigma_of(int n) {
  int m = n & 63, q = (n >> 6) * 2 + (m >= 32), k = m < 32 ? m : (m == 32 ? 0 : 64 - m);
  return (k & 1) * 64 + q * 16 + (k >> 1);
}
__device__ __forceinline__ uint4 ld_nc4(const void* p) {
  uint4 v;
  asm volatile("ld.global.nc.L1::no_allocate.v4.u32 {%0,%1,%2,%3}, [%4];" : "=r"(v.x), "=r"(v.y), "=r"(v.z), "=r"(v.w) : "l"(p));
  return v;
}
__device__ __forceinline__ uint32_t ld_nc_u16(const void* p) {
  uint32_t v;
  asm volatile("ld.global.nc.u16 %0, [%1];" : "=r"(v) : "l"(p));
  return v;
}
__device__ __forceinline__ uint4 ld_rlx4(const void* p) {
  uint4 v;
  asm volatile("ld.relaxed.gpu.global.v4.u32 {%0,%1,%2,%3}, [%4];" : "=r"(v.x), "=r"(v.y), "=r"(v.z), "=r"(v.w) : "l"(p) : "memory");
  return v;
}
__device__ __forceinline__ uint4 ld_acq4(const void* p) {
  uint4 v;
  asm volatile("ld.acquire.gpu.global.v4.u32 {%0,%1,%2,%3}, [%4];" : "=r"(v.x), "=r"(v.y), "=r"(v.z), "=r"(v.w) : "l"(p) : "memory");
  return v;
}
__device__ __forceinline__ uint32_t ld_acq1(const void* p) {
  uint32_t v;
  asm volatile("ld.acquire.gpu.global.u32 %0, [%1];" : "=r"(v) : "l"(p) : "memory");
  return v;
}
__device__ __forceinline__ void st_rel(void* p, uint32_t v) { asm volatile("st.release.gpu.global.u32 [%0], %1;" ::"l"(p), "r"(v) : "memory"); }
__device__ __forceinline__ void st_rlx(void* p, uint32_t v) { asm volatile("st.relaxed.gpu.global.u32 [%0], %1;" ::"l"(p), "r"(v) : "memory"); }
__device__ __forceinline__ void st_g4(void* p, uint32_t a, uint32_t b, uint32_t c, uint32_t d) {
  asm volatile("st.global.v4.u32 [%0], {%1,%2,%3,%4};" ::"l"(p), "r"(a), "r"(b), "r"(c), "r"(d) : "memory");
}
__device__ __forceinline__ void st_g1(void* p, uint32_t a) { asm volatile("st.global.u32 [%0], %1;" ::"l"(p), "r"(a) : "memory"); }
__device__ __forceinline__ void sts4(uint32_t a, uint32_t x, uint32_t y, uint32_t z, uint32_t w) {
  asm volatile("st.shared.v4.u32 [%0], {%1,%2,%3,%4};" ::"r"(a), "r"(x), "r"(y), "r"(z), "r"(w) : "memory");
}
__device__ __forceinline__ void sts1(uint32_t a, uint32_t x) { asm volatile("st.shared.u32 [%0], %1;" ::"r"(a), "r"(x) : "memory"); }
__device__ __forceinline__ uint4 lds4(uint32_t a) {
  uint4 v;
  asm volatile("ld.shared.v4.u32 {%0,%1,%2,%3}, [%4];" : "=r"(v.x), "=r"(v.y), "=r"(v.z), "=r"(v.w) : "r"(a) : "memory");
  return v;
}
__device__ __forceinline__ void ldsm4(uint32_t (&r)[4], uint32_t a) {
  asm volatile("ldmatrix.sync.aligned.m8n8.x4.shared.b16 {%0,%1,%2,%3}, [%4];" : "=r"(r[0]), "=r"(r[1]), "=r"(r[2]), "=r"(r[3]) : "r"(a) : "memory");
}
__device__ __forceinline__ void ldsm4t(uint32_t (&r)[4], uint32_t a) {
  asm volatile("ldmatrix.sync.aligned.m8n8.x4.trans.shared.b16 {%0,%1,%2,%3}, [%4];" : "=r"(r[0]), "=r"(r[1]), "=r"(r[2]), "=r"(r[3]) : "r"(a) : "memory");
}
__device__ __forceinline__ void stsm4(uint32_t a, uint32_t x, uint32_t y, uint32_t z, uint32_t w) {
  asm volatile("stmatrix.sync.aligned.m8n8.x4.shared.b16 [%0], {%1,%2,%3,%4};" ::"r"(a), "r"(x), "r"(y), "r"(z), "r"(w) : "memory");
}
__device__ __forceinline__ void mma16816(float (&d)[4], const uint32_t (&a)[4], uint32_t b0, uint32_t b1) {
  asm volatile("mma.sync.aligned.m16n8k16.row.col.f32.bf16.bf16.f32 {%0,%1,%2,%3}, {%4,%5,%6,%7}, {%8,%9}, {%10,%10,%10,%10};"
               : "=f"(d[0]), "=f"(d[1]), "=f"(d[2]), "=f"(d[3])
               : "r"(a[0]), "r"(a[1]), "r"(a[2]), "r"(a[3]), "r"(b0), "r"(b1), "f"(0.f));
}
__device__ __forceinline__ void wait_flags128(const uint32_t* f, uint32_t ep, int lane) {
  for (int it = 0; it < SPIN_LIMIT; it++) {
    uint4 v = ld_acq4(f + lane * 4);
    if (__all_sync(0xffffffffu, v.x == ep && v.y == ep && v.z == ep && v.w == ep)) break;
  }
}
__device__ __forceinline__ void wait_flag(const uint32_t* f, uint32_t ep) {
  for (int it = 0; it < SPIN_LIMIT; it++) {
    uint32_t v = ld_acq1(f);
    if (__all_sync(0xffffffffu, v == ep)) break;
  }
}
template <int N> __device__ __forceinline__ void load_tagged(uint4 (&v)[N], const uint32_t* const (&p)[N], uint32_t ep) {
  for (int it = 0; it < SPIN_LIMIT; it++) {
    uint32_t bad = 0;
#pragma unroll
    for (int i = 0; i < N; i++) v[i] = ld_rlx4(p[i]);
#pragma unroll
    for (int i = 0; i < N; i++) bad |= (v[i].x ^ ep) | (v[i].y ^ ep) | (v[i].z ^ ep) | (v[i].w ^ ep);
    if (__all_sync(0xffffffffu, (bad & 0xFFFF) == 0)) break;
  }
}

template <int NT> struct Acc { float e[NT * 4], o[NT * 4]; };
template <int NT> __device__ __forceinline__ void dft128(Acc<NT>& a, const uint32_t (&cs)[8][4], uint32_t tile) {
  uint64_t db = mkdesc(tile, 128, TS, 0);
  wg_fence();
#pragma unroll
  for (int j = 0; j < 8; j++) {
    if constexpr (NT == 5) wgmma_rs_n40_tb1(j < 4 ? a.e : a.o, cs[j][0], cs[j][1], cs[j][2], cs[j][3], db + j * 16, j & 3);
    else wgmma_rs_n32_tb1(j < 4 ? a.e : a.o, cs[j][0], cs[j][1], cs[j][2], cs[j][3], db + j * 16, j & 3);
  }
  wg_commit();
  wg_wait<0>();
  pin(a.e);
  pin(a.o);
}
template <bool INV, int NT> __device__ __forceinline__ void combine(const Acc<NT>& a, int j, bool k0, float (&re)[4], float (&im)[4]) {
  float per = a.e[4 * j], pei = a.e[4 * j + 1], qer = a.e[4 * j + 2], qei = a.e[4 * j + 3];
  float por = a.o[4 * j], poi = a.o[4 * j + 1], qor = a.o[4 * j + 2], qoi = a.o[4 * j + 3];
  float ar = per + por, ai = pei + poi, br = qer + qor, bi = qei + qoi;
  float cr = per - por, ci = pei - poi, dr = qer - qor, di = qei - qoi;
  constexpr int A = INV ? 3 : 0, B = INV ? 0 : 3, C = INV ? 1 : 2, D = INV ? 2 : 1;
  re[A] = ar + bi; im[A] = ai - br;
  re[B] = ar - bi; im[B] = ai + br;
  re[C] = cr + di; im[C] = ci - dr;
  re[D] = cr - di; im[D] = ci + dr;
  if (k0) {
    constexpr int M = INV ? 3 : 1, P = INV ? 1 : 3;
    re[0] = ar; im[0] = ai; re[2] = cr; im[2] = ci;
    re[M] = qer + qoi; im[M] = qei - qor;
    re[P] = qer - qoi; im[P] = qei + qor;
  }
}
__device__ __forceinline__ float silu_mul(float g, float u) {
  float e = exp2f(g * -1.4426950408889634f);
  return __fdividef(g * u, 1.f + e);
}

__global__ void __launch_bounds__(384, 1)
fused_kernel(const __grid_constant__ CUtensorMap tm1, const __grid_constant__ CUtensorMap tm3, const __grid_constant__ CUtensorMap tm2,
             const __nv_bfloat16* __restrict__ x, const __nv_bfloat16* __restrict__ wr, const __nv_bfloat16* __restrict__ wi,
             const __nv_bfloat16* __restrict__ w1, const __nv_bfloat16* __restrict__ w3, const __nv_bfloat16* __restrict__ w2,
             const __nv_bfloat16* __restrict__ cvec, const __nv_bfloat16* __restrict__ wmod, __nv_bfloat16* __restrict__ out) {
  extern __shared__ __align__(1024) unsigned char smem[];
  const uint32_t sb = s2u(smem);
  const int tid = threadIdx.x, lane = tid & 31, b = blockIdx.x;
  const uint32_t bar_full = sb + OFF_BAR, bar_empty = bar_full + NSLOT * 8;
  Scratch& S = g_s;
  STAMP(0);

  if (tid >= 256) {
    asm volatile("setmaxnreg.dec.sync.aligned.u32 56;");
    if (b == 128) return;
    const int i = tid - 256, w = i >> 5;
    uint4 v[4];
    uint32_t cr[4];
#pragma unroll
    for (int r = 0; r < 4; r++) v[r] = ld_nc4(wmod + (i + 128 * r) * 3072 + 8 * b);
#pragma unroll
    for (int r = 0; r < 4; r++) cr[r] = ld_nc_u16(cvec + i + 128 * r);
    uint32_t ep;
    asm volatile("ld.relaxed.gpu.global.u32 %0, [%1];" : "=r"(ep) : "l"(&S.epoch) : "memory");
    ep += 1;
    if (i == 0) {
      for (int s = 0; s < NSLOT; s++) { mbar_init(bar_full + s * 8, 1); mbar_init(bar_empty + s * 8, 8); }
      asm volatile("fence.mbarrier_init.release.cluster;" ::: "memory");
      asm volatile("prefetch.tensormap [%0];" ::"l"(&tm1) : "memory");
      asm volatile("prefetch.tensormap [%0];" ::"l"(&tm3) : "memory");
      asm volatile("prefetch.tensormap [%0];" ::"l"(&tm2) : "memory");
    }
    bar_arrive(7, 384);
    float sc[4];
#pragma unroll
    for (int r = 0; r < 4; r++) { float c = lo2f(cr[r]); sc[r] = bfround(__fdividef(c, 1.f + __expf(-c))); }
#pragma unroll 1
    for (int part = 0; part < 3; part++) {
      float a[8];
#pragma unroll
      for (int e = 0; e < 8; e++) a[e] = 0.f;
#pragma unroll
      for (int r = 0; r < 4; r++) {
        a[0] += sc[r] * lo2f(v[r].x); a[1] += sc[r] * hi2f(v[r].x); a[2] += sc[r] * lo2f(v[r].y); a[3] += sc[r] * hi2f(v[r].y);
        a[4] += sc[r] * lo2f(v[r].z); a[5] += sc[r] * hi2f(v[r].z); a[6] += sc[r] * lo2f(v[r].w); a[7] += sc[r] * hi2f(v[r].w);
      }
      if (part < 2) {
#pragma unroll
        for (int r = 0; r < 4; r++) v[r] = ld_nc4(wmod + (i + 128 * r) * 3072 + 1024 + 16 * b + 8 * part);
      }
      bool h4 = lane & 16, h2 = lane & 8, h1 = lane & 4;
#pragma unroll
      for (int e = 0; e < 4; e++) { float snd = h4 ? a[e] : a[e + 4], kp = h4 ? a[e + 4] : a[e]; a[e] = kp + __shfl_xor_sync(0xffffffffu, snd, 16); }
#pragma unroll
      for (int e = 0; e < 2; e++) { float snd = h2 ? a[e] : a[e + 2], kp = h2 ? a[e + 2] : a[e]; a[e] = kp + __shfl_xor_sync(0xffffffffu, snd, 8); }
      { float snd = h1 ? a[0] : a[1], kp = h1 ? a[1] : a[0]; a[0] = kp + __shfl_xor_sync(0xffffffffu, snd, 4); }
      a[0] += __shfl_xor_sync(0xffffffffu, a[0], 2);
      a[0] += __shfl_xor_sync(0xffffffffu, a[0], 1);
      if ((lane & 3) == 0) sts1(sb + OFF_RED + part * 128 + (lane >> 2) * 16 + w * 4, __float_as_uint(a[0]));
      bar_sync(6, 128);
      if (i < 8) {
        uint4 p = lds4(sb + OFF_RED + part * 128 + i * 16);
        float m = bfround((__uint_as_float(p.x) + __uint_as_float(p.y)) + (__uint_as_float(p.z) + __uint_as_float(p.w)));
        int col = part == 0 ? 8 * b + i : 1024 + 16 * b + 8 * (part - 1) + i;
        int arr = col >> 9, d = col & 511;
        if (arr == 1 || arr == 4) m = bfround(1.f + m);
        uint32_t word = __float_as_uint(m) | (ep & 0xFFFF);
        uint32_t* dst = arr < 2 ? &S.MA[(d & 127) * 8 + (arr ^ 1) * 4 + (d >> 7)]
                                : &S.MB[(((d >> 6) * 4 + ((d >> 1) & 3)) * 4 + (arr - 2)) * 16 + ((d >> 3) & 7) * 2 + (d & 1)];
        st_rlx(dst, word);
      }
      if (part == 0) {
        STAMP(1);
        if (i == 32) {
          asm volatile("cp.async.bulk.prefetch.L2.global [%0], %1;" ::"l"((const char*)w1 + b * 11008), "r"(11008) : "memory");
          asm volatile("cp.async.bulk.prefetch.L2.global [%0], %1;" ::"l"((const char*)w3 + b * 11008), "r"(11008) : "memory");
          asm volatile("cp.async.bulk.prefetch.L2.global [%0], %1;" ::"l"((const char*)w2 + b * 11008), "r"(11008) : "memory");
        }
      }
    }
    STAMP(2);
    if (i == 0) {
      const int p = b & 7;
      int slot = 0;
      uint32_t ph = 0;
#pragma unroll 1
      for (int n = 0; n < NSTAGE; n++) {
        if (slot >= NEARLY) mbar_wait(bar_empty + slot * 8, ph);
        else if (n >= NSLOT) mbar_wait(bar_empty + slot * 8, ph ^ 1);
        const uint32_t dst = sb + slot * SLOT, fb = bar_full + slot * 8;
        mbar_expect(fb, SLOT);
        if (n < 24) {
          int f0 = 176 * p + 64 * (n >> 3), k0 = 64 * (n & 7);
          tma2d(dst, &tm1, f0, k0, fb);
          tma2d(dst + 8192, &tm3, f0, k0, fb);
        } else {
          int m = n - 24, f0 = 352 * (m & 3) + 64 * (m >> 2);
          tma2d(dst, &tm2, 64 * p, f0, fb);
          tma2d(dst + 8192, &tm2, 64 * p, f0 + 176, fb);
        }
        if (++slot == NSLOT) { slot = 0; ph ^= 1; }
      }
    }
    STAMP(3);
  } else {
    asm volatile("setmaxnreg.inc.sync.aligned.u32 224;");
    const int v = tid >> 7, w = (tid >> 5) & 3, wq = tid >> 5, g = lane >> 2, t = lane & 3, i = tid & 127;
    const bool main_cta = b < 128;
    const int s0 = idx_of(b & 127);
    const uint32_t RX = sb + OFF_X, RY = sb + OFF_Y;
    uint4 xv[4];
    if (main_cta) {
      const __nv_bfloat16* xr = x + (size_t)(128 * (tid >> 4) + s0) * 512 + (lane & 15) * 8;
#pragma unroll
      for (int r = 0; r < 4; r++) xv[r] = ld_nc4(xr + 128 * r);
    }
    uint32_t ep;
    asm volatile("ld.relaxed.gpu.global.u32 %0, [%1];" : "=r"(ep) : "l"(&S.epoch) : "memory");
    ep += 1;

    const int par = w >> 1, aa = (w & 1) * 8 + g, k = 2 * aa + par;
    const bool k0 = k == 0;
    uint32_t cs[8][4];
    {
      const uint32_t NEG = 0x80008000u, m = par ? NEG : 0u;
      const uint32_t c32 = pack2(cosu(512 * k), 0.f), s32 = pack2(k0 ? 1.f : sinu(512 * k), 0.f);
#pragma unroll
      for (int pp = 0; pp < 2; pp++) {
#pragma unroll
        for (int h = 0; h < 2; h++) {
          const int kp = 2 * (2 * t + 8 * h) + pp;
          const int ks = k0 ? 32 : k, off = (k0 && pp == 0) ? 0 : 512;
          uint32_t C = pack2(cosu(16 * k * kp), cosu(16 * k * (kp + 2)));
          uint32_t Sn = pack2(cosu(16 * ks * kp - off), cosu(16 * ks * (kp + 2) - off));
          const uint32_t n1 = (k0 && pp == 0) ? 0u : NEG;
          cs[4 * pp + 0][2 * h] = C;     cs[4 * pp + 0][2 * h + 1] = Sn;
          cs[4 * pp + 1][2 * h] = C ^ m; cs[4 * pp + 1][2 * h + 1] = Sn ^ m ^ n1;
          cs[4 * pp + 2][2 * h] = C ^ m; cs[4 * pp + 2][2 * h + 1] = Sn ^ m;
          cs[4 * pp + 3][2 * h] = C;     cs[4 * pp + 3][2 * h + 1] = Sn ^ n1;
          if (pp == 0 && h == 0 && t == 0) {
            cs[1][0] = (cs[1][0] & 0xFFFF0000u) | c32;
            cs[1][1] = (cs[1][1] & 0xFFFF0000u) | s32;
            cs[3][0] = (cs[3][0] & 0xFFFF0000u) | c32;
            cs[3][1] = (cs[3][1] & 0xFFFF0000u) | (s32 ^ (n1 & 0xFFFFu));
          }
        }
      }
    }
    int bslot, bgrp;
    if (!main_cta) { bslot = 4 * v; bgrp = 8; }
    else if (b < 16) { bslot = (b >> 3) * 4; bgrp = (b & 7) + 16 * v; }
    else { int u = (b - 16) >> 4; bslot = u + 1 + (u >= 3); bgrp = (b & 15) + 16 * v; }
    uint32_t wre[4][4], wim[4][4], wre2[4], wim2[4];
    auto load_w = [&]() {
      const int ks1 = bslot < 4 ? bslot : (bslot == 4 ? 8 : bslot - 1);
      const int kd1 = idx_of(4 * bgrp + t);
#pragma unroll
      for (int q = 0; q < 4; q++) {
        const int ks = ks1 + 16 * idx_of(par * 64 + q * 16 + aa), kn = (2048 - ks) & 2047;
#pragma unroll
        for (int j = 0; j < 4; j++) {
          const int kd = 4 * kd1 + j;
          const int o = kd > 256 ? kn * 257 + 512 - kd : ks * 257 + kd;
          wre[q][j] = ld_nc_u16(wr + o);
          wim[q][j] = ld_nc_u16(wi + o);
        }
        wre2[q] = wim2[q] = 0;
        if ((kd1 & 63) == 0) { wre2[q] = ld_nc_u16(wr + kn * 257 + 4 * kd1); wim2[q] = ld_nc_u16(wi + kn * 257 + 4 * kd1); }
      }
    };

    if (main_cta) {
      uint32_t f1[6][2];
#pragma unroll
      for (int n = 0; n < 6; n++) {
        const int ks1 = n < 2 ? (g >> 1) + 4 * n : 8;
        const int p0 = 512 * (g & 1) + (n < 2 ? 0 : 512 * (n - 2) * (g >> 1));
#pragma unroll
        for (int h = 0; h < 2; h++) {
          const int s = 128 * (2 * t + 8 * h) + s0;
          f1[n][h] = pack2(cosu(s * ks1 + p0), cosu((s + 128) * ks1 + p0));
        }
      }
      const int d1 = 64 * v + 16 * w + g;
      float twc[2][4], tws[2][4];
#pragma unroll
      for (int r = 0; r < 2; r++) {
#pragma unroll
        for (int q = 0; q < 4; q++) {
          const int ph = 4 * (d1 + 8 * r) * (q ? q : t);
          twc[r][q] = cosu(ph);
          tws[r][q] = sinu(ph);
        }
      }
      STAMP(1);
      float xf[32];
#pragma unroll
      for (int r = 0; r < 4; r++) {
        xf[8 * r + 0] = lo2f(xv[r].x); xf[8 * r + 1] = hi2f(xv[r].x); xf[8 * r + 2] = lo2f(xv[r].y); xf[8 * r + 3] = hi2f(xv[r].y);
        xf[8 * r + 4] = lo2f(xv[r].z); xf[8 * r + 5] = hi2f(xv[r].z); xf[8 * r + 6] = lo2f(xv[r].w); xf[8 * r + 7] = hi2f(xv[r].w);
      }
      const uint32_t xo = (tid >> 4) * XS + (lane & 15) * 16;
#pragma unroll
      for (int r = 0; r < 4; r++) sts4(sb + OFF_XRAW + xo + 256 * r, xv[r].x, xv[r].y, xv[r].z, xv[r].w);
      STAMP(2);
      float sum = 0.f;
#pragma unroll
      for (int e = 0; e < 32; e++) sum += xf[e];
#pragma unroll
      for (int o = 8; o; o >>= 1) sum += __shfl_xor_sync(0xffffffffu, sum, o);
      const float mu = sum * (1.f / 512.f);
      float sq = 0.f;
#pragma unroll
      for (int e = 0; e < 32; e++) { xf[e] -= mu; sq += xf[e] * xf[e]; }
#pragma unroll
      for (int o = 8; o; o >>= 1) sq += __shfl_xor_sync(0xffffffffu, sq, o);
      const float rs = rsqrtf(sq * (1.f / 512.f) + 1e-5f);
#pragma unroll
      for (int r = 0; r < 4; r++)
        sts4(RX + xo + 256 * r, pack2(xf[8 * r] * rs, xf[8 * r + 1] * rs), pack2(xf[8 * r + 2] * rs, xf[8 * r + 3] * rs),
             pack2(xf[8 * r + 4] * rs, xf[8 * r + 5] * rs), pack2(xf[8 * r + 6] * rs, xf[8 * r + 7] * rs));
      bar_sync(1, 256);
      float D[4][3][4];
      {
        const uint32_t la = RX + ((lane & 7) + 8 * (lane >> 4)) * XS + (64 * v + 16 * w + (lane & 8)) * 2;
#pragma unroll
        for (int d0 = 0; d0 < 4; d0++) {
          uint32_t a[4];
          ldsm4t(a, la + 256 * d0);
          mma16816(D[d0][0], a, f1[0][0], f1[0][1]);
          mma16816(D[d0][1], a, f1[1][0], f1[1][1]);
          mma16816(D[d0][2], a, f1[2 + d0][0], f1[2 + d0][1]);
        }
      }
      load_w();
      STAMP(3);
      uint4 mv[4];
      {
        const uint32_t* const mp[4] = {&S.MA[d1 * 8], &S.MA[d1 * 8 + 4], &S.MA[d1 * 8 + 64], &S.MA[d1 * 8 + 68]};
        load_tagged<4>(mv, mp, ep);
      }
      STAMP(4);
#pragma unroll
      for (int r = 0; r < 2; r++) {
        const float m[4] = {hi2f(mv[2 * r].x), hi2f(mv[2 * r].y), hi2f(mv[2 * r].z), hi2f(mv[2 * r].w)};
        const float z = t == 0 ? 16.f : 0.f;
        const float ad[4] = {z * hi2f(mv[2 * r + 1].x), z * hi2f(mv[2 * r + 1].y), z * hi2f(mv[2 * r + 1].z), z * hi2f(mv[2 * r + 1].w)};
        const uint32_t row = RY + sigma_of(d1 + 8 * r) * 16;
#pragma unroll
        for (int n = 0; n < 2; n++) {
          float vr[4], vi[4];
#pragma unroll
          for (int d0 = 0; d0 < 4; d0++) {
            vr[d0] = n == 0 ? fmaf(D[d0][n][2 * r], m[d0], ad[d0]) : D[d0][n][2 * r] * m[d0];
            vi[d0] = D[d0][n][2 * r + 1] * m[d0];
          }
          const float Ar = vr[0] + vr[2], Ai = vi[0] + vi[2], Br = vr[0] - vr[2], Bi = vi[0] - vi[2];
          const float Cr = vr[1] + vr[3], Ci = vi[1] + vi[3], Er = vr[1] - vr[3], Ei = vi[1] - vi[3];
          const float orr[4] = {Ar + Cr, Br + Ei, Ar - Cr, Br - Ei}, oi[4] = {Ai + Ci, Bi - Er, Ai - Ci, Bi + Er};
          uint32_t pk[4];
          pk[0] = pack2(orr[0], oi[0]);
#pragma unroll
          for (int q = 1; q < 4; q++) pk[q] = pack2(orr[q] * twc[r][q] + oi[q] * tws[r][q], oi[q] * twc[r][q] - orr[q] * tws[r][q]);
          sts4(row + (t + 5 * n) * TS, pk[0], pk[1], pk[2], pk[3]);
        }
        float er = 0.f, ei = 0.f;
#pragma unroll
        for (int d0 = 0; d0 < 4; d0++) { er = fmaf(D[d0][2][2 * r], m[d0], er); ei = fmaf(D[d0][2][2 * r + 1], m[d0], ei); }
        sts1(row + 4 * TS + 4 * t, pack2(er * twc[r][0] + ei * tws[r][0], ei * twc[r][0] - er * tws[r][0]));
      }
      fence_async_smem();
      bar_sync(1, 256);
      STAMP(5);
      {
        Acc<5> acc;
        dft128<5>(acc, cs, RY + 5 * v * TS);
        STAMP(6);
        uint32_t* gp = &S.G[(b * 9 + 5 * v) * 512 + (par * 16 + (aa >> 2)) * 16 + t * 4 + (aa & 3)];
#pragma unroll
        for (int j = 0; j < 5; j++) {
          if (j < 4 || v == 0) {
            float re[4], im[4];
            combine<false>(acc, j, k0, re, im);
            const bool half = v == 0 && (j == 0 || j == 4);
#pragma unroll
            for (int q = 0; q < 4; q++)
              if (q < 2 || !half || (q == 2 && w == 0)) st_g1(gp + j * 512 + q * 64, pack2(re[q], im[q]));
          }
        }
      }
      bar_sync(2 + v, 128);
      if (i == 0) st_rel(&S.flagG[v * 128 + b], ep);
      STAMP(7);
    } else {
      load_w();
    }

    float wfr[4][4], wfi[4][4];
    {
      const int kd1 = idx_of(4 * bgrp + t);
      const bool half = (bslot & 3) == 0 && bslot < 8;
#pragma unroll
      for (int q = 0; q < 4; q++) {
#pragma unroll
        for (int j = 0; j < 4; j++) {
          const bool mir = 4 * kd1 + j > 256;
          const float sc = (mir && half) ? 0.f : 1.f;
          wfr[q][j] = lo2f(wre[q][j]) * sc;
          wfi[q][j] = lo2f(wim[q][j]) * (mir ? -sc : sc);
        }
        if ((kd1 & 63) == 0) {
          const float sc = half ? 0.25f : 0.5f;
          wfr[q][0] = (wfr[q][0] + lo2f(wre2[q])) * sc;
          wfi[q][0] = (wfi[q][0] - lo2f(wim2[q])) * sc;
        }
      }
    }
    STAMP(8);
    wait_flags128(&S.flagG[bslot >= 5 ? 128 : 0], ep, lane);
    STAMP(9);
    {
      const uint32_t* gp = &S.G[((i >> 2) * 9 + bslot) * 512 + bgrp * 16 + (i & 3) * 4];
      uint4 gv[4];
#pragma unroll
      for (int r = 0; r < 4; r++) gv[r] = ld_rlx4(gp + r * 32 * 9 * 512);
      const uint32_t dst = RX + (5 * v + (i & 3)) * TS + (i >> 2) * 16;
#pragma unroll
      for (int r = 0; r < 4; r++) sts4(dst + r * 512, gv[r].x, gv[r].y, gv[r].z, gv[r].w);
    }
    fence_async_smem();
    bar_sync(2 + v, 128);
    STAMP(10);
    {
      Acc<4> acc;
      dft128<4>(acc, cs, RX + 5 * v * TS);
      const uint32_t dst = RY + 5 * v * TS + (par * 64 + (lane >> 3) * 16 + (w & 1) * 8 + (lane & 7)) * 16;
#pragma unroll
      for (int j = 0; j < 4; j++) {
        float re[4], im[4];
        combine<false>(acc, j, k0, re, im);
        uint32_t pk[4];
#pragma unroll
        for (int q = 0; q < 4; q++) pk[q] = pack2(re[q] * wfr[q][j] - im[q] * wfi[q][j], re[q] * wfi[q][j] + im[q] * wfr[q][j]);
        stsm4(dst + j * TS, pk[0], pk[1], pk[2], pk[3]);
      }
      fence_async_smem();
      bar_sync(2 + v, 128);
      STAMP(11);
      dft128<4>(acc, cs, RY + 5 * v * TS);
      uint32_t pk[4][4];
#pragma unroll
      for (int j = 0; j < 4; j++) {
        float re[4], im[4];
        combine<true>(acc, j, k0, re, im);
#pragma unroll
        for (int q = 0; q < 4; q++) pk[q][j] = pack2(re[q], im[q]);
      }
      uint32_t* zp = &S.Z[((par * 64 + aa) * 9 + bslot) * 512 + (4 * bgrp + t) * 4];
#pragma unroll
      for (int q = 0; q < 4; q++) st_g4(zp + q * 16 * 9 * 512, pk[q][0], pk[q][1], pk[q][2], pk[q][3]);
    }
    bar_sync(2 + v, 128);
    if (i == 0) st_rel(&S.flagZ[2 * b + v], ep);
    STAMP(12);
    if (!main_cta) return;

    uint32_t fm[5][4];
#pragma unroll
    for (int n = 0; n < 10; n++) {
      const int ks1 = n < 4 ? n : (n == 4 ? 8 : n - 1);
#pragma unroll
      for (int r = 0; r < 2; r++) {
        const int ph = (128 * (g + 8 * r) + s0) * ks1 + 512 * w * t;
        fm[n >> 1][2 * (n & 1) + r] = n < 9 ? pack2(cosu(ph), cosu(ph + 512)) : 0u;
      }
    }
    float tc[4], tsn[4];
#pragma unroll
    for (int q = 0; q < 4; q++) {
      const int ph = 4 * idx_of(par * 64 + q * 16 + aa) * t;
      tc[q] = cosu(ph);
      tsn[q] = sinu(ph);
    }
    uint32_t mg[3][8];
    {
      const uint32_t* mb = &S.MB[((2 * w + v) * 4 + t) * 64];
#pragma unroll
      for (int a = 0; a < 3; a++) {
        uint4 mv[4];
        const uint32_t* const mp[4] = {mb + a * 16, mb + a * 16 + 4, mb + a * 16 + 8, mb + a * 16 + 12};
        load_tagged<4>(mv, mp, ep);
#pragma unroll
        for (int e = 0; e < 4; e++) { mg[a][2 * e] = __byte_perm(mv[e].x, mv[e].y, 0x7632); mg[a][2 * e + 1] = __byte_perm(mv[e].z, mv[e].w, 0x7632); }
      }
    }
    uint32_t xa[4][4];
    {
      const uint32_t la = sb + OFF_XRAW + (lane & 15) * XS + (128 * w + 64 * v + (lane >> 4) * 8) * 2;
#pragma unroll
      for (int jj = 0; jj < 4; jj++) ldsm4(xa[jj], la + 32 * jj);
    }
    STAMP(13);
    wait_flags128(&S.flagZ[128 * v], ep, lane);
    if (v == 0) wait_flag(&S.flagZ[256 + (lane & 1)], ep);
    STAMP(14);
    {
      const uint32_t* zb = &S.Z[b * 9 * 512];
      uint4 zv[5];
      const int hs = (i >> 6) * 4, sg = (i & 31) + 2 * (i & 32);
      const int sl3 = v ? 8 : hs, sg3 = v ? i : sg;
#pragma unroll
      for (int r = 0; r < 3; r++) zv[r] = ld_rlx4(zb + (1 + 4 * v + r) * 512 + i * 4);
      zv[3] = ld_rlx4(zb + sl3 * 512 + sg3 * 4);
      zv[4] = make_uint4(0, 0, 0, 0);
      if (v == 0 && (i & 63) == 0) zv[4] = ld_rlx4(zb + hs * 512 + 32 * 4);
#pragma unroll
      for (int r = 0; r < 3; r++) sts4(RX + (1 + 4 * v + r) * TS + i * 16, zv[r].x, zv[r].y, zv[r].z, zv[r].w);
      sts4(RX + sl3 * TS + sg3 * 16, zv[3].x, zv[3].y, zv[3].z, zv[3].w);
      if (v == 0) sts4(RX + hs * TS + (sg + 32) * 16, zv[4].x, zv[4].y, zv[4].z, zv[4].w);
    }
    fence_async_smem();
    bar_sync(2 + v, 128);
    STAMP(15);
    {
      Acc<5> acc;
      dft128<5>(acc, cs, RX + 5 * v * TS);
      const uint32_t dst = RY + 5 * v * TS + idx_of(par * 64 + (lane >> 3) * 16 + (w & 1) * 8 + (lane & 7)) * 16;
#pragma unroll
      for (int j = 0; j < 5; j++) {
        if (j < 4 || v == 0) {
          float re[4], im[4];
          combine<true>(acc, j, k0, re, im);
          uint32_t pk[4];
#pragma unroll
          for (int q = 0; q < 4; q++) pk[q] = pack2(re[q] * tc[q] - im[q] * tsn[q], re[q] * tsn[q] + im[q] * tc[q]);
          stsm4(dst + j * TS, pk[0], pk[1], pk[2], pk[3]);
        }
      }
    }
    fence_async_smem();
    bar_sync(1, 256);
    STAMP(16);
    {
      float y[32];
      wg_fence();
#pragma unroll
      for (int n = 0; n < 5; n++)
        wgmma_rs_n64_tb0(y, fm[n][0], fm[n][1], fm[n][2], fm[n][3], mkdesc(RY + 2 * n * TS + 1024 * v, n < 4 ? TS : 0, 128, 0), n);
      wg_commit();
      wg_wait<0>();
      pin(y);
      STAMP(17);
      float sm[2] = {0.f, 0.f};
#pragma unroll
      for (int j = 0; j < 8; j++) {
        const float g0 = lo2f(mg[0][j]) * 0x1p-19f, g1 = hi2f(mg[0][j]) * 0x1p-19f;
#pragma unroll
        for (int r = 0; r < 2; r++) {
          const uint32_t xx = xa[j >> 1][2 * (j & 1) + r];
          y[4 * j + 2 * r] = fmaf(y[4 * j + 2 * r], g0, lo2f(xx));
          y[4 * j + 2 * r + 1] = fmaf(y[4 * j + 2 * r + 1], g1, hi2f(xx));
          sm[r] += y[4 * j + 2 * r] + y[4 * j + 2 * r + 1];
        }
      }
      float m2[2] = {0.f, 0.f};
#pragma unroll
      for (int r = 0; r < 2; r++) {
        sm[r] *= (1.f / 16.f);
#pragma unroll
        for (int j = 0; j < 8; j++) {
          const float u0 = y[4 * j + 2 * r] - sm[r], u1 = y[4 * j + 2 * r + 1] - sm[r];
          m2[r] += u0 * u0 + u1 * u1;
        }
#pragma unroll
        for (int o = 1; o < 4; o <<= 1) {
          const float om = __shfl_xor_sync(0xffffffffu, sm[r], o), oq = __shfl_xor_sync(0xffffffffu, m2[r], o);
          const float dl = sm[r] - om;
          m2[r] += oq + dl * dl * (8.f * o);
          sm[r] = 0.5f * (sm[r] + om);
        }
      }
      if (t < 2) {
        const uint32_t a = sb + OFF_STAT + (g + 8 * t) * 64 + wq * 8;
        asm volatile("st.shared.v2.f32 [%0], {%1,%2};" ::"r"(a), "f"(t ? sm[1] : sm[0]), "f"(t ? m2[1] : m2[0]) : "memory");
      }
      const int fo = (b * 32 + 8 * w + 4 * v) * 32 + lane;
#pragma unroll
      for (int jj = 0; jj < 4; jj++)
        st_g4(&S.X1[fo + jj * 32], pack2(y[8 * jj], y[8 * jj + 1]), pack2(y[8 * jj + 2], y[8 * jj + 3]), pack2(y[8 * jj + 4], y[8 * jj + 5]),
              pack2(y[8 * jj + 6], y[8 * jj + 7]));
      bar_sync(1, 256);
      float mu[2], rs[2];
#pragma unroll
      for (int r = 0; r < 2; r++) {
        float mm[8], q = 0.f, ms = 0.f;
#pragma unroll
        for (int e = 0; e < 4; e++) {
          uint4 sv = lds4(sb + OFF_STAT + (g + 8 * r) * 64 + e * 16);
          mm[2 * e] = __uint_as_float(sv.x); mm[2 * e + 1] = __uint_as_float(sv.z);
          q += __uint_as_float(sv.y) + __uint_as_float(sv.w);
          ms += mm[2 * e] + mm[2 * e + 1];
        }
        mu[r] = ms * 0.125f;
        float dq = 0.f;
#pragma unroll
        for (int e = 0; e < 8; e++) dq += (mm[e] - mu[r]) * (mm[e] - mu[r]);
        rs[r] = rsqrtf((q + 64.f * dq) * (1.f / 512.f) + 1e-5f);
      }
      uint32_t hp[16];
#pragma unroll
      for (int j = 0; j < 8; j++) {
#pragma unroll
        for (int r = 0; r < 2; r++)
          hp[2 * j + r] = pack2(fmaf((y[4 * j + 2 * r] - mu[r]) * rs[r], lo2f(mg[2][j]), lo2f(mg[1][j])),
                                fmaf((y[4 * j + 2 * r + 1] - mu[r]) * rs[r], hi2f(mg[2][j]), hi2f(mg[1][j])));
      }
#pragma unroll
      for (int jj = 0; jj < 4; jj++) st_g4(&S.H2[fo + jj * 32], hp[4 * jj], hp[4 * jj + 1], hp[4 * jj + 2], hp[4 * jj + 3]);
    }
    __syncwarp();
    if (lane == 0) st_rel(&S.flagH2[b * 8 + wq], ep);
    bar_sync(7, 384);
    if (lane == 0) {
#pragma unroll
      for (int s = NEARLY; s < NSLOT; s++) mbar_arrive(bar_empty + s * 8);
    }
    STAMP(18);

    const int p = b & 7, beta = (b & ~7) + wq;
    wait_flag(&S.flagH2[beta * 8 + (lane & 7)], ep);
    STAMP(19);
    uint4 A[32];
#pragma unroll
    for (int n = 0; n < 32; n++) A[n] = ld_rlx4(&S.H2[(beta * 32 + n) * 32 + lane]);
    uint4* hdst = &S.H[(beta * 88 + 11 * p) * 32 + lane];
    const uint4* hsrc = &S.H[beta * 88 * 32 + lane];
    uint32_t* fl = &S.flagH[beta * 8];
    if (v == 1) bar_sync(4, 256);
#define SLOT_OF(n) ((n) % NSLOT)
#define PHASE_OF(n) (((n) / NSLOT) & 1)
#pragma unroll
    for (int c = 0; c < 2; c++) {
      float acc[64];
#pragma unroll
      for (int kb = 0; kb < 8; kb++) {
        const int n = 8 * c + kb;
        mbar_wait(bar_full + SLOT_OF(n) * 8, PHASE_OF(n));
        const uint64_t db = mkdesc(sb + SLOT_OF(n) * SLOT, 8192, 1024, 1);
        wg_fence();
#pragma unroll
        for (int j = 0; j < 4; j++) { const uint4 a = A[4 * kb + j]; wgmma_rs_n128_tb1(acc, a.x, a.y, a.z, a.w, db + j * 128, kb | j); }
        wg_commit();
        if (c == 0 && kb == 1 && v == 0) bar_arrive(4, 256);
        if (c == 1 && kb == 1) { if (lane == 0) st_rel(fl + p, ep); __syncwarp(); }
        if (kb > 0) { wg_wait<1>(); if (lane == 0) mbar_arrive(bar_empty + SLOT_OF(n - 1) * 8); }
      }
      wg_wait<0>();
      pin(acc);
      if (lane == 0) mbar_arrive(bar_empty + SLOT_OF(8 * c + 7) * 8);
      STAMP(20 + 2 * c);
#pragma unroll
      for (int jj = 0; jj < 4; jj++) {
        float h[8];
#pragma unroll
        for (int e = 0; e < 8; e++) h[e] = silu_mul(acc[8 * jj + e], acc[32 + 8 * jj + e]);
        st_g4(hdst + (4 * c + jj) * 32, pack2(h[0], h[1]), pack2(h[2], h[3]), pack2(h[4], h[5]), pack2(h[6], h[7]));
      }
      __syncwarp();
      STAMP(21 + 2 * c);
    }
    uint4 B2[24][4];
    {
      float ag[24], au[24];
#pragma unroll
      for (int kb = 0; kb < 8; kb++) {
        const int n = 16 + kb;
        mbar_wait(bar_full + SLOT_OF(n) * 8, PHASE_OF(n));
        const uint64_t db = mkdesc(sb + SLOT_OF(n) * SLOT, 8192, 1024, 1);
        wg_fence();
#pragma unroll
        for (int j = 0; j < 4; j++) {
          const uint4 a = A[4 * kb + j];
          wgmma_rs_n48_tb1(ag, a.x, a.y, a.z, a.w, db + j * 128, kb | j);
          wgmma_rs_n48_tb1(au, a.x, a.y, a.z, a.w, db + 512 + j * 128, kb | j);
        }
        wg_commit();
        if (kb == 1) { if (lane == 0) st_rel(fl + 1024 + p, ep); __syncwarp(); }
        if (kb == 6) wait_flag(fl + (lane & 7), ep);
        if (kb > 0) { wg_wait<1>(); if (lane == 0) mbar_arrive(bar_empty + SLOT_OF(n - 1) * 8); }
      }
      wg_wait<0>();
      pin(ag);
      pin(au);
      if (lane == 0) mbar_arrive(bar_empty + SLOT_OF(23) * 8);
      STAMP(24);
#pragma unroll
      for (int m = 0; m < 8; m++) {
#pragma unroll
        for (int j = 0; j < 4; j++) B2[m][j] = ld_rlx4(hsrc + (11 * m + j) * 32);
      }
#pragma unroll
      for (int jj = 0; jj < 3; jj++) {
        float h[8];
#pragma unroll
        for (int e = 0; e < 8; e++) h[e] = silu_mul(ag[8 * jj + e], au[8 * jj + e]);
        st_g4(hdst + (8 + jj) * 32, pack2(h[0], h[1]), pack2(h[2], h[3]), pack2(h[4], h[5]), pack2(h[6], h[7]));
      }
      __syncwarp();
      STAMP(25);
    }
    {
      float acc[32];
      uint4 x1v[4], gbv[4];
#pragma unroll
      for (int st = 0; st < 12; st++) {
        const int n = 24 + st;
        mbar_wait(bar_full + SLOT_OF(n) * 8, PHASE_OF(n));
        const uint64_t db = mkdesc(sb + SLOT_OF(n) * SLOT, 8192, 1024, 1);
        wg_fence();
#pragma unroll
        for (int u = 0; u < 2; u++) {
          const int m = 2 * st + u, nk = m < 16 ? 4 : (m < 23 ? 3 : 1);
#pragma unroll
          for (int j = 0; j < 4; j++)
            if (j < nk) { const uint4 a = B2[m][j]; wgmma_rs_n64_tb1(acc, a.x, a.y, a.z, a.w, db + u * 512 + j * 128, m | j); }
        }
        wg_commit();
        if (st == 0) { if (lane == 0) st_rel(fl + 2048 + p, ep); __syncwarp(); wait_flag(fl + 1024 + (lane & 7), ep); }
        if (st == 4) wait_flag(fl + 2048 + (lane & 7), ep);
        wg_wait<0>();
        if (st < 8) {
#pragma unroll
          for (int u = 0; u < 2; u++) {
            const int m = 8 + 2 * st + u, nk = m < 16 ? 4 : (m < 23 ? 3 : 1);
#pragma unroll
            for (int j = 0; j < 4; j++)
              if (j < nk) B2[m][j] = ld_rlx4(hsrc + (11 * (m & 7) + 4 * (m >> 3) + j) * 32);
          }
        }
        if (st == 8) {
#pragma unroll
          for (int jj = 0; jj < 4; jj++) x1v[jj] = ld_rlx4(&S.X1[(beta * 32 + 4 * p + jj) * 32 + lane]);
          const uint32_t* mb = &S.MB[(p * 4 + t) * 64 + 48];
          const uint32_t* const mp[4] = {mb, mb + 4, mb + 8, mb + 12};
          load_tagged<4>(gbv, mp, ep);
        }
      }
      wg_wait<0>();
      pin(acc);
      STAMP(26);
      const uint32_t stg = sb + OFF_XRAW + wq * 2048;
#pragma unroll
      for (int jj = 0; jj < 4; jj++) {
        const uint32_t xx[4] = {x1v[jj].x, x1v[jj].y, x1v[jj].z, x1v[jj].w};
        const uint32_t gg[4] = {gbv[jj].x, gbv[jj].y, gbv[jj].z, gbv[jj].w};
        uint32_t pk[4];
#pragma unroll
        for (int e = 0; e < 4; e++)
          pk[e] = pack2(fmaf(acc[8 * jj + 2 * e], hi2f(gg[e & 2]), lo2f(xx[e])), fmaf(acc[8 * jj + 2 * e + 1], hi2f(gg[(e & 2) + 1]), hi2f(xx[e])));
        stsm4(stg + (lane & 15) * 128 + (((2 * jj + (lane >> 4)) ^ (lane & 7)) << 4), pk[0], pk[1], pk[2], pk[3]);
      }
      __syncwarp();
      __nv_bfloat16* op = out + (size_t)idx_of(beta) * 512 + 64 * p + (lane & 7) * 8;
#pragma unroll
      for (int r = 0; r < 4; r++) {
        const int row = 4 * r + (lane >> 3);
        uint4 o = lds4(stg + row * 128 + (((lane & 7) ^ (row & 7)) << 4));
        st_g4(op + (size_t)row * 128 * 512, o.x, o.y, o.z, o.w);
      }
    }
    if (b == 0 && tid == 0) st_rlx(&S.epoch, ep);
    STAMP(27);
  }
}

typedef CUresult (*EncodeFn)(CUtensorMap*, CUtensorMapDataType, cuuint32_t, void*, const cuuint64_t*, const cuuint64_t*, const cuuint32_t*,
                             const cuuint32_t*, CUtensorMapInterleave, CUtensorMapSwizzle, CUtensorMapL2promotion, CUtensorMapFloatOOBfill);

void make_map(EncodeFn fn, CUtensorMap* m, const void* base, uint64_t inner, uint64_t outer) {
  cuuint64_t dims[2] = {inner, outer};
  cuuint64_t strides[1] = {inner * 2};
  cuuint32_t box[2] = {64, 64};
  cuuint32_t es[2] = {1, 1};
  fn(m, CU_TENSOR_MAP_DATA_TYPE_BFLOAT16, 2, const_cast<void*>(base), dims, strides, box, es, CU_TENSOR_MAP_INTERLEAVE_NONE,
     CU_TENSOR_MAP_SWIZZLE_128B, CU_TENSOR_MAP_L2_PROMOTION_L2_128B, CU_TENSOR_MAP_FLOAT_OOB_FILL_NONE);
}

}

extern "C" void kernel_launch(void* const* d_in, const int* in_sizes, int n_in, void* d_out, int out_size) {
  static EncodeFn fn = nullptr;
  if (!fn) {
    cudaDriverEntryPointQueryResult qr;
    void* p = nullptr;
    cudaGetDriverEntryPoint("cuTensorMapEncodeTiled", &p, cudaEnableDefault, &qr);
    fn = (EncodeFn)p;
    cudaFuncSetAttribute(fused_kernel, cudaFuncAttributeMaxDynamicSharedMemorySize, SMEM_BYTES);
  }
  typedef const __nv_bfloat16* P;
  CUtensorMap tm1, tm3, tm2;
  make_map(fn, &tm1, d_in[4], 1376, 512);
  make_map(fn, &tm3, d_in[5], 1376, 512);
  make_map(fn, &tm2, d_in[6], 512, 1376);
  fused_kernel<<<NCTA, 384, SMEM_BYTES>>>(tm1, tm3, tm2, (P)d_in[0], (P)d_in[1], (P)d_in[2], (P)d_in[4], (P)d_in[5], (P)d_in[6], (P)d_in[7],
                                          (P)d_in[8], (__nv_bfloat16*)d_out);
}
```

```cpp
#include <cuda_runtime.h>
#include <cuda_bf16.h>
#include <cuda.h>
#include <stdint.h>

__device__ __forceinline__ void wgmma_rs_n128_tb1(float (&d)[64], uint32_t a0, uint32_t a1, uint32_t a2, uint32_t a3, uint64_t db, int scale_d) {
  asm volatile("{\n.reg .pred p;\nsetp.ne.b32 p, %69, 0;\n"
    "wgmma.mma_async.sync.aligned.m64n128k16.f32.bf16.bf16 {%0, %1, %2, %3, %4, %5, %6, %7, %8, %9, %10, %11, %12, %13, %14, %15, %16, %17, %18, %19, %20, %21, %22, %23, %24, %25, %26, %27, %28, %29, %30, %31, %32, %33, %34, %35, %36, %37, %38, %39, %40, %41, %42, %43, %44, %45, %46, %47, %48, %49, %50, %51, %52, %53, %54, %55, %56, %57, %58, %59, %60, %61, %62, %63}, {%64, %65, %66, %67}, %68, p, 1, 1, 1;\n}\n"
    : "+f"(d[0]), "+f"(d[1]), "+f"(d[2]), "+f"(d[3]), "+f"(d[4]), "+f"(d[5]), "+f"(d[6]), "+f"(d[7]), "+f"(d[8]), "+f"(d[9]), "+f"(d[10]), "+f"(d[11]), "+f"(d[12]), "+f"(d[13]), "+f"(d[14]), "+f"(d[15]), "+f"(d[16]), "+f"(d[17]), "+f"(d[18]), "+f"(d[19]), "+f"(d[20]), "+f"(d[21]), "+f"(d[22]), "+f"(d[23]), "+f"(d[24]), "+f"(d[25]), "+f"(d[26]), "+f"(d[27]), "+f"(d[28]), "+f"(d[29]), "+f"(d[30]), "+f"(d[31]), "+f"(d[32]), "+f"(d[33]), "+f"(d[34]), "+f"(d[35]), "+f"(d[36]), "+f"(d[37]), "+f"(d[38]), "+f"(d[39]), "+f"(d[40]), "+f"(d[41]), "+f"(d[42]), "+f"(d[43]), "+f"(d[44]), "+f"(d[45]), "+f"(d[46]), "+f"(d[47]), "+f"(d[48]), "+f"(d[49]), "+f"(d[50]), "+f"(d[51]), "+f"(d[52]), "+f"(d[53]), "+f"(d[54]), "+f"(d[55]), "+f"(d[56]), "+f"(d[57]), "+f"(d[58]), "+f"(d[59]), "+f"(d[60]), "+f"(d[61]), "+f"(d[62]), "+f"(d[63])
    : "r"(a0), "r"(a1), "r"(a2), "r"(a3), "l"(db), "r"(scale_d));
}
__device__ __forceinline__ void wgmma_rs_n64_tb1(float (&d)[32], uint32_t a0, uint32_t a1, uint32_t a2, uint32_t a3, uint64_t db, int scale_d) {
  asm volatile("{\n.reg .pred p;\nsetp.ne.b32 p, %37, 0;\n"
    "wgmma.mma_async.sync.aligned.m64n64k16.f32.bf16.bf16 {%0, %1, %2, %3, %4, %5, %6, %7, %8, %9, %10, %11, %12, %13, %14, %15, %16, %17, %18, %19, %20, %21, %22, %23, %24, %25, %26, %27, %28, %29, %30, %31}, {%32, %33, %34, %35}, %36, p, 1, 1, 1;\n}\n"
    : "+f"(d[0]), "+f"(d[1]), "+f"(d[2]), "+f"(d[3]), "+f"(d[4]), "+f"(d[5]), "+f"(d[6]), "+f"(d[7]), "+f"(d[8]), "+f"(d[9]), "+f"(d[10]), "+f"(d[11]), "+f"(d[12]), "+f"(d[13]), "+f"(d[14]), "+f"(d[15]), "+f"(d[16]), "+f"(d[17]), "+f"(d[18]), "+f"(d[19]), "+f"(d[20]), "+f"(d[21]), "+f"(d[22]), "+f"(d[23]), "+f"(d[24]), "+f"(d[25]), "+f"(d[26]), "+f"(d[27]), "+f"(d[28]), "+f"(d[29]), "+f"(d[30]), "+f"(d[31])
    : "r"(a0), "r"(a1), "r"(a2), "r"(a3), "l"(db), "r"(scale_d));
}
__device__ __forceinline__ void wgmma_rs_n48_tb1(float (&d)[24], uint32_t a0, uint32_t a1, uint32_t a2, uint32_t a3, uint64_t db, int scale_d) {
  asm volatile("{\n.reg .pred p;\nsetp.ne.b32 p, %29, 0;\n"
    "wgmma.mma_async.sync.aligned.m64n48k16.f32.bf16.bf16 {%0, %1, %2, %3, %4, %5, %6, %7, %8, %9, %10, %11, %12, %13, %14, %15, %16, %17, %18, %19, %20, %21, %22, %23}, {%24, %25, %26, %27}, %28, p, 1, 1, 1;\n}\n"
    : "+f"(d[0]), "+f"(d[1]), "+f"(d[2]), "+f"(d[3]), "+f"(d[4]), "+f"(d[5]), "+f"(d[6]), "+f"(d[7]), "+f"(d[8]), "+f"(d[9]), "+f"(d[10]), "+f"(d[11]), "+f"(d[12]), "+f"(d[13]), "+f"(d[14]), "+f"(d[15]), "+f"(d[16]), "+f"(d[17]), "+f"(d[18]), "+f"(d[19]), "+f"(d[20]), "+f"(d[21]), "+f"(d[22]), "+f"(d[23])
    : "r"(a0), "r"(a1), "r"(a2), "r"(a3), "l"(db), "r"(scale_d));
}
__device__ __forceinline__ void wgmma_rs_n32_tb1(float (&d)[16], uint32_t a0, uint32_t a1, uint32_t a2, uint32_t a3, uint64_t db, int scale_d) {
  asm volatile("{\n.reg .pred p;\nsetp.ne.b32 p, %21, 0;\n"
    "wgmma.mma_async.sync.aligned.m64n32k16.f32.bf16.bf16 {%0, %1, %2, %3, %4, %5, %6, %7, %8, %9, %10, %11, %12, %13, %14, %15}, {%16, %17, %18, %19}, %20, p, 1, 1, 1;\n}\n"
    : "+f"(d[0]), "+f"(d[1]), "+f"(d[2]), "+f"(d[3]), "+f"(d[4]), "+f"(d[5]), "+f"(d[6]), "+f"(d[7]), "+f"(d[8]), "+f"(d[9]), "+f"(d[10]), "+f"(d[11]), "+f"(d[12]), "+f"(d[13]), "+f"(d[14]), "+f"(d[15])
    : "r"(a0), "r"(a1), "r"(a2), "r"(a3), "l"(db), "r"(scale_d));
}
__device__ __forceinline__ void wgmma_rs_n40_tb1(float (&d)[20], uint32_t a0, uint32_t a1, uint32_t a2, uint32_t a3, uint64_t db, int scale_d) {
  asm volatile("{\n.reg .pred p;\nsetp.ne.b32 p, %25, 0;\n"
    "wgmma.mma_async.sync.aligned.m64n40k16.f32.bf16.bf16 {%0, %1, %2, %3, %4, %5, %6, %7, %8, %9, %10, %11, %12, %13, %14, %15, %16, %17, %18, %19}, {%20, %21, %22, %23}, %24, p, 1, 1, 1;\n}\n"
    : "+f"(d[0]), "+f"(d[1]), "+f"(d[2]), "+f"(d[3]), "+f"(d[4]), "+f"(d[5]), "+f"(d[6]), "+f"(d[7]), "+f"(d[8]), "+f"(d[9]), "+f"(d[10]), "+f"(d[11]), "+f"(d[12]), "+f"(d[13]), "+f"(d[14]), "+f"(d[15]), "+f"(d[16]), "+f"(d[17]), "+f"(d[18]), "+f"(d[19])
    : "r"(a0), "r"(a1), "r"(a2), "r"(a3), "l"(db), "r"(scale_d));
}
__device__ __forceinline__ void wgmma_rs_n64_tb0(float (&d)[32], uint32_t a0, uint32_t a1, uint32_t a2, uint32_t a3, uint64_t db, int scale_d) {
  asm volatile("{\n.reg .pred p;\nsetp.ne.b32 p, %37, 0;\n"
    "wgmma.mma_async.sync.aligned.m64n64k16.f32.bf16.bf16 {%0, %1, %2, %3, %4, %5, %6, %7, %8, %9, %10, %11, %12, %13, %14, %15, %16, %17, %18, %19, %20, %21, %22, %23, %24, %25, %26, %27, %28, %29, %30, %31}, {%32, %33, %34, %35}, %36, p, 1, 1, 0;\n}\n"
    : "+f"(d[0]), "+f"(d[1]), "+f"(d[2]), "+f"(d[3]), "+f"(d[4]), "+f"(d[5]), "+f"(d[6]), "+f"(d[7]), "+f"(d[8]), "+f"(d[9]), "+f"(d[10]), "+f"(d[11]), "+f"(d[12]), "+f"(d[13]), "+f"(d[14]), "+f"(d[15]), "+f"(d[16]), "+f"(d[17]), "+f"(d[18]), "+f"(d[19]), "+f"(d[20]), "+f"(d[21]), "+f"(d[22]), "+f"(d[23]), "+f"(d[24]), "+f"(d[25]), "+f"(d[26]), "+f"(d[27]), "+f"(d[28]), "+f"(d[29]), "+f"(d[30]), "+f"(d[31])
    : "r"(a0), "r"(a1), "r"(a2), "r"(a3), "l"(db), "r"(scale_d));
}

__device__ __forceinline__ void settle_g(uint4* v, const uint4* p, uint32_t tag, uint32_t dst) {
  asm volatile("{\n.reg .pred p;\n.reg .b32 c, bad, o<8>;\n"
    "xor.b32 %0, %0, %17;\nst.shared.v4.u32 [%18+0], {%0,%1,%2,%3};\nxor.b32 %4, %4, %17;\nst.shared.v4.u32 [%18+256], {%4,%5,%6,%7};\nxor.b32 %8, %8, %17;\nst.shared.v4.u32 [%18+512], {%8,%9,%10,%11};\nxor.b32 %12, %12, %17;\nst.shared.v4.u32 [%18+768], {%12,%13,%14,%15};\nlop3.b32 o0, %0, %4, %8, 0xFE;\nlop3.b32 bad, o0, %12, 65537, 0xA8;\nsetp.ne.u32 p, bad, 0;\nvote.sync.any.pred p, p, 0xffffffff;\n@!p bra.uni DS;\n"
    "mov.u32 c, 131072;\nLS:\n"
    "ld.relaxed.gpu.global.v4.u32 {%0,%1,%2,%3}, [%16+0];\n"
    "ld.relaxed.gpu.global.v4.u32 {%4,%5,%6,%7}, [%16+528384];\n"
    "ld.relaxed.gpu.global.v4.u32 {%8,%9,%10,%11}, [%16+1056768];\n"
    "ld.relaxed.gpu.global.v4.u32 {%12,%13,%14,%15}, [%16+1585152];\n"
    "xor.b32 %0, %0, %17;\nst.shared.v4.u32 [%18+0], {%0,%1,%2,%3};\nxor.b32 %4, %4, %17;\nst.shared.v4.u32 [%18+256], {%4,%5,%6,%7};\nxor.b32 %8, %8, %17;\nst.shared.v4.u32 [%18+512], {%8,%9,%10,%11};\nxor.b32 %12, %12, %17;\nst.shared.v4.u32 [%18+768], {%12,%13,%14,%15};\nlop3.b32 o0, %0, %4, %8, 0xFE;\nlop3.b32 bad, o0, %12, 65537, 0xA8;\nadd.u32 c, c, -1;\nsetp.ne.u32 p, c, 0;\nsetp.ne.and.u32 p, bad, 0, p;\nvote.sync.any.pred p, p, 0xffffffff;\n@p bra.uni LS;\nDS:\n}"
    : "+r"(v[0].x), "+r"(v[0].y), "+r"(v[0].z), "+r"(v[0].w), "+r"(v[1].x), "+r"(v[1].y), "+r"(v[1].z), "+r"(v[1].w), "+r"(v[2].x), "+r"(v[2].y), "+r"(v[2].z), "+r"(v[2].w), "+r"(v[3].x), "+r"(v[3].y), "+r"(v[3].z), "+r"(v[3].w)
    : "l"(p), "r"(tag), "r"(dst) : "memory");
}
__device__ __forceinline__ void settle_z(uint4* v, const uint4* p, const uint4* p2, uint32_t tag, uint32_t dst, uint32_t dst0) {
  asm volatile("{\n.reg .pred p;\n.reg .b32 c, bad, o<8>;\n.reg .pred e;\nsetp.ne.u64 e, %20, %22;\n"
    "xor.b32 %0, %0, %21;\nst.shared.v4.u32 [%24], {%0,%1,%2,%3};\nxor.b32 %4, %4, %21;\nst.shared.v4.u32 [%23+2160], {%4,%5,%6,%7};\nxor.b32 %8, %8, %21;\nst.shared.v4.u32 [%23+4320], {%8,%9,%10,%11};\nxor.b32 %12, %12, %21;\nst.shared.v4.u32 [%23+6480], {%12,%13,%14,%15};\nxor.b32 %16, %16, %21;\n@e st.shared.v4.u32 [%24+512], {%16,%17,%18,%19};\nlop3.b32 o0, %0, %4, %8, 0xFE;\nlop3.b32 o1, o0, %12, %16, 0xFE;\nlop3.b32 bad, o1, o1, 65537, 0xA8;\nsetp.ne.u32 p, bad, 0;\nvote.sync.any.pred p, p, 0xffffffff;\n@!p bra.uni DS;\n"
    "mov.u32 c, 131072;\nLS:\n"
    "ld.relaxed.gpu.global.v4.u32 {%0,%1,%2,%3}, [%20+0];\n"
    "ld.relaxed.gpu.global.v4.u32 {%4,%5,%6,%7}, [%20+2048];\n"
    "ld.relaxed.gpu.global.v4.u32 {%8,%9,%10,%11}, [%20+4096];\n"
    "ld.relaxed.gpu.global.v4.u32 {%12,%13,%14,%15}, [%20+6144];\n"
    "ld.relaxed.gpu.global.v4.u32 {%16,%17,%18,%19}, [%22];\n"
    "xor.b32 %0, %0, %21;\nst.shared.v4.u32 [%24], {%0,%1,%2,%3};\nxor.b32 %4, %4, %21;\nst.shared.v4.u32 [%23+2160], {%4,%5,%6,%7};\nxor.b32 %8, %8, %21;\nst.shared.v4.u32 [%23+4320], {%8,%9,%10,%11};\nxor.b32 %12, %12, %21;\nst.shared.v4.u32 [%23+6480], {%12,%13,%14,%15};\nxor.b32 %16, %16, %21;\n@e st.shared.v4.u32 [%24+512], {%16,%17,%18,%19};\nlop3.b32 o0, %0, %4, %8, 0xFE;\nlop3.b32 o1, o0, %12, %16, 0xFE;\nlop3.b32 bad, o1, o1, 65537, 0xA8;\nadd.u32 c, c, -1;\nsetp.ne.u32 p, c, 0;\nsetp.ne.and.u32 p, bad, 0, p;\nvote.sync.any.pred p, p, 0xffffffff;\n@p bra.uni LS;\nDS:\n}"
    : "+r"(v[0].x), "+r"(v[0].y), "+r"(v[0].z), "+r"(v[0].w), "+r"(v[1].x), "+r"(v[1].y), "+r"(v[1].z), "+r"(v[1].w), "+r"(v[2].x), "+r"(v[2].y), "+r"(v[2].z), "+r"(v[2].w), "+r"(v[3].x), "+r"(v[3].y), "+r"(v[3].z), "+r"(v[3].w), "+r"(v[4].x), "+r"(v[4].y), "+r"(v[4].z), "+r"(v[4].w)
    : "l"(p), "r"(tag), "l"(p2), "r"(dst), "r"(dst0) : "memory");
}
__device__ __forceinline__ void settle4_32(uint4* v, const uint4* p, uint32_t tag) {
  asm volatile("{\n.reg .pred p;\n.reg .b32 c, bad, o<8>;\n"
    "xor.b32 %0, %0, %17;\nxor.b32 %4, %4, %17;\nxor.b32 %8, %8, %17;\nxor.b32 %12, %12, %17;\nlop3.b32 o0, %0, %4, %8, 0xFE;\nlop3.b32 bad, o0, %12, 65537, 0xA8;\nsetp.ne.u32 p, bad, 0;\nvote.sync.any.pred p, p, 0xffffffff;\n@!p bra.uni DS;\n"
    "mov.u32 c, 131072;\nLS:\n"
    "ld.relaxed.gpu.global.v4.u32 {%0,%1,%2,%3}, [%16+0];\n"
    "ld.relaxed.gpu.global.v4.u32 {%4,%5,%6,%7}, [%16+512];\n"
    "ld.relaxed.gpu.global.v4.u32 {%8,%9,%10,%11}, [%16+1024];\n"
    "ld.relaxed.gpu.global.v4.u32 {%12,%13,%14,%15}, [%16+1536];\n"
    "xor.b32 %0, %0, %17;\nxor.b32 %4, %4, %17;\nxor.b32 %8, %8, %17;\nxor.b32 %12, %12, %17;\nlop3.b32 o0, %0, %4, %8, 0xFE;\nlop3.b32 bad, o0, %12, 65537, 0xA8;\nadd.u32 c, c, -1;\nsetp.ne.u32 p, c, 0;\nsetp.ne.and.u32 p, bad, 0, p;\nvote.sync.any.pred p, p, 0xffffffff;\n@p bra.uni LS;\nDS:\n}"
    : "+r"(v[0].x), "+r"(v[0].y), "+r"(v[0].z), "+r"(v[0].w), "+r"(v[1].x), "+r"(v[1].y), "+r"(v[1].z), "+r"(v[1].w), "+r"(v[2].x), "+r"(v[2].y), "+r"(v[2].z), "+r"(v[2].w), "+r"(v[3].x), "+r"(v[3].y), "+r"(v[3].z), "+r"(v[3].w)
    : "l"(p), "r"(tag) : "memory");
}
__device__ __forceinline__ void fetch16_32(uint4* v, const uint4* p, uint32_t tag) {
  asm volatile("{\n.reg .pred p;\n.reg .b32 c, bad, o<8>;\n"
    "mov.u32 c, 131072;\nLS:\n"
    "ld.relaxed.gpu.global.v4.u32 {%0,%1,%2,%3}, [%64+0];\n"
    "ld.relaxed.gpu.global.v4.u32 {%4,%5,%6,%7}, [%64+512];\n"
    "ld.relaxed.gpu.global.v4.u32 {%8,%9,%10,%11}, [%64+1024];\n"
    "ld.relaxed.gpu.global.v4.u32 {%12,%13,%14,%15}, [%64+1536];\n"
    "ld.relaxed.gpu.global.v4.u32 {%16,%17,%18,%19}, [%64+2048];\n"
    "ld.relaxed.gpu.global.v4.u32 {%20,%21,%22,%23}, [%64+2560];\n"
    "ld.relaxed.gpu.global.v4.u32 {%24,%25,%26,%27}, [%64+3072];\n"
    "ld.relaxed.gpu.global.v4.u32 {%28,%29,%30,%31}, [%64+3584];\n"
    "ld.relaxed.gpu.global.v4.u32 {%32,%33,%34,%35}, [%64+4096];\n"
    "ld.relaxed.gpu.global.v4.u32 {%36,%37,%38,%39}, [%64+4608];\n"
    "ld.relaxed.gpu.global.v4.u32 {%40,%41,%42,%43}, [%64+5120];\n"
    "ld.relaxed.gpu.global.v4.u32 {%44,%45,%46,%47}, [%64+5632];\n"
    "ld.relaxed.gpu.global.v4.u32 {%48,%49,%50,%51}, [%64+6144];\n"
    "ld.relaxed.gpu.global.v4.u32 {%52,%53,%54,%55}, [%64+6656];\n"
    "ld.relaxed.gpu.global.v4.u32 {%56,%57,%58,%59}, [%64+7168];\n"
    "ld.relaxed.gpu.global.v4.u32 {%60,%61,%62,%63}, [%64+7680];\n"
    "xor.b32 %0, %0, %65;\nxor.b32 %4, %4, %65;\nxor.b32 %8, %8, %65;\nxor.b32 %12, %12, %65;\nxor.b32 %16, %16, %65;\nxor.b32 %20, %20, %65;\nxor.b32 %24, %24, %65;\nxor.b32 %28, %28, %65;\nxor.b32 %32, %32, %65;\nxor.b32 %36, %36, %65;\nxor.b32 %40, %40, %65;\nxor.b32 %44, %44, %65;\nxor.b32 %48, %48, %65;\nxor.b32 %52, %52, %65;\nxor.b32 %56, %56, %65;\nxor.b32 %60, %60, %65;\nlop3.b32 o0, %0, %4, %8, 0xFE;\nlop3.b32 o1, %12, %16, %20, 0xFE;\nlop3.b32 o2, %24, %28, %32, 0xFE;\nlop3.b32 o3, %36, %40, %44, 0xFE;\nlop3.b32 o4, %48, %52, %56, 0xFE;\nlop3.b32 o5, o0, o1, o2, 0xFE;\nlop3.b32 o6, o3, o4, %60, 0xFE;\nlop3.b32 bad, o5, o6, 65537, 0xA8;\nadd.u32 c, c, -1;\nsetp.ne.u32 p, c, 0;\nsetp.ne.and.u32 p, bad, 0, p;\nvote.sync.any.pred p, p, 0xffffffff;\n@p bra.uni LS;\nDS:\n}"
    : "=r"(v[0].x), "=r"(v[0].y), "=r"(v[0].z), "=r"(v[0].w), "=r"(v[1].x), "=r"(v[1].y), "=r"(v[1].z), "=r"(v[1].w), "=r"(v[2].x), "=r"(v[2].y), "=r"(v[2].z), "=r"(v[2].w), "=r"(v[3].x), "=r"(v[3].y), "=r"(v[3].z), "=r"(v[3].w), "=r"(v[4].x), "=r"(v[4].y), "=r"(v[4].z), "=r"(v[4].w), "=r"(v[5].x), "=r"(v[5].y), "=r"(v[5].z), "=r"(v[5].w), "=r"(v[6].x), "=r"(v[6].y), "=r"(v[6].z), "=r"(v[6].w), "=r"(v[7].x), "=r"(v[7].y), "=r"(v[7].z), "=r"(v[7].w), "=r"(v[8].x), "=r"(v[8].y), "=r"(v[8].z), "=r"(v[8].w), "=r"(v[9].x), "=r"(v[9].y), "=r"(v[9].z), "=r"(v[9].w), "=r"(v[10].x), "=r"(v[10].y), "=r"(v[10].z), "=r"(v[10].w), "=r"(v[11].x), "=r"(v[11].y), "=r"(v[11].z), "=r"(v[11].w), "=r"(v[12].x), "=r"(v[12].y), "=r"(v[12].z), "=r"(v[12].w), "=r"(v[13].x), "=r"(v[13].y), "=r"(v[13].z), "=r"(v[13].w), "=r"(v[14].x), "=r"(v[14].y), "=r"(v[14].z), "=r"(v[14].w), "=r"(v[15].x), "=r"(v[15].y), "=r"(v[15].z), "=r"(v[15].w)
    : "l"(p), "r"(tag) : "memory");
}
__device__ __forceinline__ void settle16_32(uint4* v, const uint4* p, uint32_t tag) {
  asm volatile("{\n.reg .pred p;\n.reg .b32 c, bad, o<8>;\n"
    "xor.b32 %0, %0, %65;\nxor.b32 %4, %4, %65;\nxor.b32 %8, %8, %65;\nxor.b32 %12, %12, %65;\nxor.b32 %16, %16, %65;\nxor.b32 %20, %20, %65;\nxor.b32 %24, %24, %65;\nxor.b32 %28, %28, %65;\nxor.b32 %32, %32, %65;\nxor.b32 %36, %36, %65;\nxor.b32 %40, %40, %65;\nxor.b32 %44, %44, %65;\nxor.b32 %48, %48, %65;\nxor.b32 %52, %52, %65;\nxor.b32 %56, %56, %65;\nxor.b32 %60, %60, %65;\nlop3.b32 o0, %0, %4, %8, 0xFE;\nlop3.b32 o1, %12, %16, %20, 0xFE;\nlop3.b32 o2, %24, %28, %32, 0xFE;\nlop3.b32 o3, %36, %40, %44, 0xFE;\nlop3.b32 o4, %48, %52, %56, 0xFE;\nlop3.b32 o5, o0, o1, o2, 0xFE;\nlop3.b32 o6, o3, o4, %60, 0xFE;\nlop3.b32 bad, o5, o6, 65537, 0xA8;\nsetp.ne.u32 p, bad, 0;\nvote.sync.any.pred p, p, 0xffffffff;\n@!p bra.uni DS;\n"
    "mov.u32 c, 131072;\nLS:\n"
    "ld.relaxed.gpu.global.v4.u32 {%0,%1,%2,%3}, [%64+0];\n"
    "ld.relaxed.gpu.global.v4.u32 {%4,%5,%6,%7}, [%64+512];\n"
    "ld.relaxed.gpu.global.v4.u32 {%8,%9,%10,%11}, [%64+1024];\n"
    "ld.relaxed.gpu.global.v4.u32 {%12,%13,%14,%15}, [%64+1536];\n"
    "ld.relaxed.gpu.global.v4.u32 {%16,%17,%18,%19}, [%64+2048];\n"
    "ld.relaxed.gpu.global.v4.u32 {%20,%21,%22,%23}, [%64+2560];\n"
    "ld.relaxed.gpu.global.v4.u32 {%24,%25,%26,%27}, [%64+3072];\n"
    "ld.relaxed.gpu.global.v4.u32 {%28,%29,%30,%31}, [%64+3584];\n"
    "ld.relaxed.gpu.global.v4.u32 {%32,%33,%34,%35}, [%64+4096];\n"
    "ld.relaxed.gpu.global.v4.u32 {%36,%37,%38,%39}, [%64+4608];\n"
    "ld.relaxed.gpu.global.v4.u32 {%40,%41,%42,%43}, [%64+5120];\n"
    "ld.relaxed.gpu.global.v4.u32 {%44,%45,%46,%47}, [%64+5632];\n"
    "ld.relaxed.gpu.global.v4.u32 {%48,%49,%50,%51}, [%64+6144];\n"
    "ld.relaxed.gpu.global.v4.u32 {%52,%53,%54,%55}, [%64+6656];\n"
    "ld.relaxed.gpu.global.v4.u32 {%56,%57,%58,%59}, [%64+7168];\n"
    "ld.relaxed.gpu.global.v4.u32 {%60,%61,%62,%63}, [%64+7680];\n"
    "xor.b32 %0, %0, %65;\nxor.b32 %4, %4, %65;\nxor.b32 %8, %8, %65;\nxor.b32 %12, %12, %65;\nxor.b32 %16, %16, %65;\nxor.b32 %20, %20, %65;\nxor.b32 %24, %24, %65;\nxor.b32 %28, %28, %65;\nxor.b32 %32, %32, %65;\nxor.b32 %36, %36, %65;\nxor.b32 %40, %40, %65;\nxor.b32 %44, %44, %65;\nxor.b32 %48, %48, %65;\nxor.b32 %52, %52, %65;\nxor.b32 %56, %56, %65;\nxor.b32 %60, %60, %65;\nlop3.b32 o0, %0, %4, %8, 0xFE;\nlop3.b32 o1, %12, %16, %20, 0xFE;\nlop3.b32 o2, %24, %28, %32, 0xFE;\nlop3.b32 o3, %36, %40, %44, 0xFE;\nlop3.b32 o4, %48, %52, %56, 0xFE;\nlop3.b32 o5, o0, o1, o2, 0xFE;\nlop3.b32 o6, o3, o4, %60, 0xFE;\nlop3.b32 bad, o5, o6, 65537, 0xA8;\nadd.u32 c, c, -1;\nsetp.ne.u32 p, c, 0;\nsetp.ne.and.u32 p, bad, 0, p;\nvote.sync.any.pred p, p, 0xffffffff;\n@p bra.uni LS;\nDS:\n}"
    : "+r"(v[0].x), "+r"(v[0].y), "+r"(v[0].z), "+r"(v[0].w), "+r"(v[1].x), "+r"(v[1].y), "+r"(v[1].z), "+r"(v[1].w), "+r"(v[2].x), "+r"(v[2].y), "+r"(v[2].z), "+r"(v[2].w), "+r"(v[3].x), "+r"(v[3].y), "+r"(v[3].z), "+r"(v[3].w), "+r"(v[4].x), "+r"(v[4].y), "+r"(v[4].z), "+r"(v[4].w), "+r"(v[5].x), "+r"(v[5].y), "+r"(v[5].z), "+r"(v[5].w), "+r"(v[6].x), "+r"(v[6].y), "+r"(v[6].z), "+r"(v[6].w), "+r"(v[7].x), "+r"(v[7].y), "+r"(v[7].z), "+r"(v[7].w), "+r"(v[8].x), "+r"(v[8].y), "+r"(v[8].z), "+r"(v[8].w), "+r"(v[9].x), "+r"(v[9].y), "+r"(v[9].z), "+r"(v[9].w), "+r"(v[10].x), "+r"(v[10].y), "+r"(v[10].z), "+r"(v[10].w), "+r"(v[11].x), "+r"(v[11].y), "+r"(v[11].z), "+r"(v[11].w), "+r"(v[12].x), "+r"(v[12].y), "+r"(v[12].z), "+r"(v[12].w), "+r"(v[13].x), "+r"(v[13].y), "+r"(v[13].z), "+r"(v[13].w), "+r"(v[14].x), "+r"(v[14].y), "+r"(v[14].z), "+r"(v[14].w), "+r"(v[15].x), "+r"(v[15].y), "+r"(v[15].z), "+r"(v[15].w)
    : "l"(p), "r"(tag) : "memory");
}
__device__ __forceinline__ void settle_h0(uint4* v, const uint4* const (&p)[4], uint32_t tag) {
  asm volatile("{\n.reg .pred p;\n.reg .b32 c, bad, o<8>;\n"
    "xor.b32 %0, %0, %51;\nxor.b32 %4, %4, %51;\nxor.b32 %8, %8, %51;\nxor.b32 %12, %12, %51;\nxor.b32 %16, %16, %51;\nxor.b32 %20, %20, %51;\nxor.b32 %24, %24, %51;\nxor.b32 %28, %28, %51;\nxor.b32 %32, %32, %51;\nxor.b32 %36, %36, %51;\nxor.b32 %40, %40, %51;\nxor.b32 %44, %44, %51;\nlop3.b32 o0, %0, %4, %8, 0xFE;\nlop3.b32 o1, %12, %16, %20, 0xFE;\nlop3.b32 o2, %24, %28, %32, 0xFE;\nlop3.b32 o3, %36, %40, %44, 0xFE;\nlop3.b32 o4, o0, o1, o2, 0xFE;\nlop3.b32 bad, o4, o3, 65537, 0xA8;\nsetp.ne.u32 p, bad, 0;\nvote.sync.any.pred p, p, 0xffffffff;\n@!p bra.uni DS;\n"
    "mov.u32 c, 131072;\nLS:\n"
    "ld.relaxed.gpu.global.v4.u32 {%0,%1,%2,%3}, [%48+0];\n"
    "ld.relaxed.gpu.global.v4.u32 {%4,%5,%6,%7}, [%48+512];\n"
    "ld.relaxed.gpu.global.v4.u32 {%8,%9,%10,%11}, [%48+1024];\n"
    "ld.relaxed.gpu.global.v4.u32 {%12,%13,%14,%15}, [%48+1536];\n"
    "ld.relaxed.gpu.global.v4.u32 {%16,%17,%18,%19}, [%49+0];\n"
    "ld.relaxed.gpu.global.v4.u32 {%20,%21,%22,%23}, [%49+512];\n"
    "ld.relaxed.gpu.global.v4.u32 {%24,%25,%26,%27}, [%49+1024];\n"
    "ld.relaxed.gpu.global.v4.u32 {%28,%29,%30,%31}, [%49+1536];\n"
    "ld.relaxed.gpu.global.v4.u32 {%32,%33,%34,%35}, [%50+0];\n"
    "ld.relaxed.gpu.global.v4.u32 {%36,%37,%38,%39}, [%50+512];\n"
    "ld.relaxed.gpu.global.v4.u32 {%40,%41,%42,%43}, [%50+1024];\n"
    "ld.relaxed.gpu.global.v4.u32 {%44,%45,%46,%47}, [%50+1536];\n"
    "xor.b32 %0, %0, %51;\nxor.b32 %4, %4, %51;\nxor.b32 %8, %8, %51;\nxor.b32 %12, %12, %51;\nxor.b32 %16, %16, %51;\nxor.b32 %20, %20, %51;\nxor.b32 %24, %24, %51;\nxor.b32 %28, %28, %51;\nxor.b32 %32, %32, %51;\nxor.b32 %36, %36, %51;\nxor.b32 %40, %40, %51;\nxor.b32 %44, %44, %51;\nlop3.b32 o0, %0, %4, %8, 0xFE;\nlop3.b32 o1, %12, %16, %20, 0xFE;\nlop3.b32 o2, %24, %28, %32, 0xFE;\nlop3.b32 o3, %36, %40, %44, 0xFE;\nlop3.b32 o4, o0, o1, o2, 0xFE;\nlop3.b32 bad, o4, o3, 65537, 0xA8;\nadd.u32 c, c, -1;\nsetp.ne.u32 p, c, 0;\nsetp.ne.and.u32 p, bad, 0, p;\nvote.sync.any.pred p, p, 0xffffffff;\n@p bra.uni LS;\nDS:\n}"
    : "+r"(v[0].x), "+r"(v[0].y), "+r"(v[0].z), "+r"(v[0].w), "+r"(v[1].x), "+r"(v[1].y), "+r"(v[1].z), "+r"(v[1].w), "+r"(v[2].x), "+r"(v[2].y), "+r"(v[2].z), "+r"(v[2].w), "+r"(v[3].x), "+r"(v[3].y), "+r"(v[3].z), "+r"(v[3].w), "+r"(v[4].x), "+r"(v[4].y), "+r"(v[4].z), "+r"(v[4].w), "+r"(v[5].x), "+r"(v[5].y), "+r"(v[5].z), "+r"(v[5].w), "+r"(v[6].x), "+r"(v[6].y), "+r"(v[6].z), "+r"(v[6].w), "+r"(v[7].x), "+r"(v[7].y), "+r"(v[7].z), "+r"(v[7].w), "+r"(v[8].x), "+r"(v[8].y), "+r"(v[8].z), "+r"(v[8].w), "+r"(v[9].x), "+r"(v[9].y), "+r"(v[9].z), "+r"(v[9].w), "+r"(v[10].x), "+r"(v[10].y), "+r"(v[10].z), "+r"(v[10].w), "+r"(v[11].x), "+r"(v[11].y), "+r"(v[11].z), "+r"(v[11].w)
    : "l"(p[1]), "l"(p[2]), "l"(p[3]), "r"(tag) : "memory");
}
__device__ __forceinline__ void settle_h1(uint4* v, const uint4* const (&p)[4], uint32_t tag) {
  asm volatile("{\n.reg .pred p;\n.reg .b32 c, bad, o<8>;\n"
    "xor.b32 %0, %0, %51;\nxor.b32 %4, %4, %51;\nxor.b32 %8, %8, %51;\nxor.b32 %12, %12, %51;\nxor.b32 %16, %16, %51;\nxor.b32 %20, %20, %51;\nxor.b32 %24, %24, %51;\nxor.b32 %28, %28, %51;\nxor.b32 %32, %32, %51;\nxor.b32 %36, %36, %51;\nxor.b32 %40, %40, %51;\nxor.b32 %44, %44, %51;\nlop3.b32 o0, %0, %4, %8, 0xFE;\nlop3.b32 o1, %12, %16, %20, 0xFE;\nlop3.b32 o2, %24, %28, %32, 0xFE;\nlop3.b32 o3, %36, %40, %44, 0xFE;\nlop3.b32 o4, o0, o1, o2, 0xFE;\nlop3.b32 bad, o4, o3, 65537, 0xA8;\nsetp.ne.u32 p, bad, 0;\nvote.sync.any.pred p, p, 0xffffffff;\n@!p bra.uni DS;\n"
    "mov.u32 c, 131072;\nLS:\n"
    "ld.relaxed.gpu.global.v4.u32 {%0,%1,%2,%3}, [%48+2048];\n"
    "ld.relaxed.gpu.global.v4.u32 {%4,%5,%6,%7}, [%48+2560];\n"
    "ld.relaxed.gpu.global.v4.u32 {%8,%9,%10,%11}, [%48+3072];\n"
    "ld.relaxed.gpu.global.v4.u32 {%12,%13,%14,%15}, [%48+3584];\n"
    "ld.relaxed.gpu.global.v4.u32 {%16,%17,%18,%19}, [%49+2048];\n"
    "ld.relaxed.gpu.global.v4.u32 {%20,%21,%22,%23}, [%49+2560];\n"
    "ld.relaxed.gpu.global.v4.u32 {%24,%25,%26,%27}, [%49+3072];\n"
    "ld.relaxed.gpu.global.v4.u32 {%28,%29,%30,%31}, [%49+3584];\n"
    "ld.relaxed.gpu.global.v4.u32 {%32,%33,%34,%35}, [%50+2048];\n"
    "ld.relaxed.gpu.global.v4.u32 {%36,%37,%38,%39}, [%50+2560];\n"
    "ld.relaxed.gpu.global.v4.u32 {%40,%41,%42,%43}, [%50+3072];\n"
    "ld.relaxed.gpu.global.v4.u32 {%44,%45,%46,%47}, [%50+3584];\n"
    "xor.b32 %0, %0, %51;\nxor.b32 %4, %4, %51;\nxor.b32 %8, %8, %51;\nxor.b32 %12, %12, %51;\nxor.b32 %16, %16, %51;\nxor.b32 %20, %20, %51;\nxor.b32 %24, %24, %51;\nxor.b32 %28, %28, %51;\nxor.b32 %32, %32, %51;\nxor.b32 %36, %36, %51;\nxor.b32 %40, %40, %51;\nxor.b32 %44, %44, %51;\nlop3.b32 o0, %0, %4, %8, 0xFE;\nlop3.b32 o1, %12, %16, %20, 0xFE;\nlop3.b32 o2, %24, %28, %32, 0xFE;\nlop3.b32 o3, %36, %40, %44, 0xFE;\nlop3.b32 o4, o0, o1, o2, 0xFE;\nlop3.b32 bad, o4, o3, 65537, 0xA8;\nadd.u32 c, c, -1;\nsetp.ne.u32 p, c, 0;\nsetp.ne.and.u32 p, bad, 0, p;\nvote.sync.any.pred p, p, 0xffffffff;\n@p bra.uni LS;\nDS:\n}"
    : "+r"(v[0].x), "+r"(v[0].y), "+r"(v[0].z), "+r"(v[0].w), "+r"(v[1].x), "+r"(v[1].y), "+r"(v[1].z), "+r"(v[1].w), "+r"(v[2].x), "+r"(v[2].y), "+r"(v[2].z), "+r"(v[2].w), "+r"(v[3].x), "+r"(v[3].y), "+r"(v[3].z), "+r"(v[3].w), "+r"(v[4].x), "+r"(v[4].y), "+r"(v[4].z), "+r"(v[4].w), "+r"(v[5].x), "+r"(v[5].y), "+r"(v[5].z), "+r"(v[5].w), "+r"(v[6].x), "+r"(v[6].y), "+r"(v[6].z), "+r"(v[6].w), "+r"(v[7].x), "+r"(v[7].y), "+r"(v[7].z), "+r"(v[7].w), "+r"(v[8].x), "+r"(v[8].y), "+r"(v[8].z), "+r"(v[8].w), "+r"(v[9].x), "+r"(v[9].y), "+r"(v[9].z), "+r"(v[9].w), "+r"(v[10].x), "+r"(v[10].y), "+r"(v[10].z), "+r"(v[10].w), "+r"(v[11].x), "+r"(v[11].y), "+r"(v[11].z), "+r"(v[11].w)
    : "l"(p[1]), "l"(p[2]), "l"(p[3]), "r"(tag) : "memory");
}
__device__ __forceinline__ void settle_h2(uint4* v, const uint4* const (&p)[4], uint32_t tag) {
  asm volatile("{\n.reg .pred p;\n.reg .b32 c, bad, o<8>;\n"
    "xor.b32 %0, %0, %39;\nxor.b32 %4, %4, %39;\nxor.b32 %8, %8, %39;\nxor.b32 %12, %12, %39;\nxor.b32 %16, %16, %39;\nxor.b32 %20, %20, %39;\nxor.b32 %24, %24, %39;\nxor.b32 %28, %28, %39;\nxor.b32 %32, %32, %39;\nlop3.b32 o0, %0, %4, %8, 0xFE;\nlop3.b32 o1, %12, %16, %20, 0xFE;\nlop3.b32 o2, %24, %28, %32, 0xFE;\nlop3.b32 o3, o0, o1, o2, 0xFE;\nlop3.b32 bad, o3, o3, 65537, 0xA8;\nsetp.ne.u32 p, bad, 0;\nvote.sync.any.pred p, p, 0xffffffff;\n@!p bra.uni DS;\n"
    "mov.u32 c, 131072;\nLS:\n"
    "ld.relaxed.gpu.global.v4.u32 {%0,%1,%2,%3}, [%36+4096];\n"
    "ld.relaxed.gpu.global.v4.u32 {%4,%5,%6,%7}, [%36+4608];\n"
    "ld.relaxed.gpu.global.v4.u32 {%8,%9,%10,%11}, [%36+5120];\n"
    "ld.relaxed.gpu.global.v4.u32 {%12,%13,%14,%15}, [%37+4096];\n"
    "ld.relaxed.gpu.global.v4.u32 {%16,%17,%18,%19}, [%37+4608];\n"
    "ld.relaxed.gpu.global.v4.u32 {%20,%21,%22,%23}, [%37+5120];\n"
    "ld.relaxed.gpu.global.v4.u32 {%24,%25,%26,%27}, [%38+4096];\n"
    "ld.relaxed.gpu.global.v4.u32 {%28,%29,%30,%31}, [%38+4608];\n"
    "ld.relaxed.gpu.global.v4.u32 {%32,%33,%34,%35}, [%38+5120];\n"
    "xor.b32 %0, %0, %39;\nxor.b32 %4, %4, %39;\nxor.b32 %8, %8, %39;\nxor.b32 %12, %12, %39;\nxor.b32 %16, %16, %39;\nxor.b32 %20, %20, %39;\nxor.b32 %24, %24, %39;\nxor.b32 %28, %28, %39;\nxor.b32 %32, %32, %39;\nlop3.b32 o0, %0, %4, %8, 0xFE;\nlop3.b32 o1, %12, %16, %20, 0xFE;\nlop3.b32 o2, %24, %28, %32, 0xFE;\nlop3.b32 o3, o0, o1, o2, 0xFE;\nlop3.b32 bad, o3, o3, 65537, 0xA8;\nadd.u32 c, c, -1;\nsetp.ne.u32 p, c, 0;\nsetp.ne.and.u32 p, bad, 0, p;\nvote.sync.any.pred p, p, 0xffffffff;\n@p bra.uni LS;\nDS:\n}"
    : "+r"(v[0].x), "+r"(v[0].y), "+r"(v[0].z), "+r"(v[0].w), "+r"(v[1].x), "+r"(v[1].y), "+r"(v[1].z), "+r"(v[1].w), "+r"(v[2].x), "+r"(v[2].y), "+r"(v[2].z), "+r"(v[2].w), "+r"(v[3].x), "+r"(v[3].y), "+r"(v[3].z), "+r"(v[3].w), "+r"(v[4].x), "+r"(v[4].y), "+r"(v[4].z), "+r"(v[4].w), "+r"(v[5].x), "+r"(v[5].y), "+r"(v[5].z), "+r"(v[5].w), "+r"(v[6].x), "+r"(v[6].y), "+r"(v[6].z), "+r"(v[6].w), "+r"(v[7].x), "+r"(v[7].y), "+r"(v[7].z), "+r"(v[7].w), "+r"(v[8].x), "+r"(v[8].y), "+r"(v[8].z), "+r"(v[8].w)
    : "l"(p[1]), "l"(p[2]), "l"(p[3]), "r"(tag) : "memory");
}

namespace {

constexpr int NCTA = 129;
constexpr int TS = 2160;
constexpr int ODD = 1088;
constexpr int XS = 1040;
constexpr int NSLOT = 11;
constexpr int SLOT = 16384;
constexpr int NSTAGE = 36;
constexpr int NEARLY = NSLOT - 5;
constexpr int OFF_WM = (NEARLY - 1) * SLOT;
constexpr int OFF_W = NEARLY * SLOT;
constexpr int OFF_X = OFF_W + 2 * SLOT;
constexpr int OFF_Y = OFF_X + 9 * TS;
constexpr int OFF_MA = OFF_Y + 9 * TS;
constexpr int OFF_XRAW = NSLOT * SLOT;
constexpr int OFF_STAT = OFF_XRAW + 16 * XS;
constexpr int OFF_RED = OFF_STAT + 1152;
constexpr int OFF_GB = OFF_RED + 384;
constexpr int OFF_EP = OFF_GB + 512;
constexpr int OFF_BAR = OFF_EP + 64;
constexpr int SMEM_BYTES = OFF_BAR + (2 * NSLOT + 2 + 8) * 8;
static_assert(OFF_MA + 128 * 48 + 32 <= NSLOT * SLOT, "scratch overflows ring");
static_assert(SMEM_BYTES <= 195 * 1024, "smem");
constexpr uint32_t SB = 1024;
constexpr int SPIN_LIMIT = 1 << 17;
constexpr int ES = 1032;
constexpr uint32_t TAGM = 0x00010001u;

struct __align__(1024) Scratch {
  uint4 E[NCTA * ES];
  uint4 X1[128 * 32 * 32];
  uint4 H[128 * 88 * 32];
  uint32_t M[8 * 3072];
  uint32_t epoch[NCTA * 8];
};
__device__ Scratch g_s;

__device__ __forceinline__ uint32_t s2u(const void* p) { return (uint32_t)__cvta_generic_to_shared(p); }
__device__ __forceinline__ void wg_fence() { asm volatile("wgmma.fence.sync.aligned;" ::: "memory"); }
__device__ __forceinline__ void wg_commit() { asm volatile("wgmma.commit_group.sync.aligned;" ::: "memory"); }
template <int N> __device__ __forceinline__ void wg_wait() { asm volatile("wgmma.wait_group.sync.aligned %0;" ::"n"(N) : "memory"); }
template <int N> __device__ __forceinline__ void pin(float (&d)[N]) {
#pragma unroll
  for (int i = 0; i < N; i++) asm volatile("" : "+f"(d[i])::"memory");
}
__device__ __forceinline__ uint32_t as_u(uint32_t v) { return v; }
__device__ __forceinline__ uint32_t as_u(float v) { return __float_as_uint(v); }
template <class T, int N> __device__ __forceinline__ void keep(const T* d, uint32_t never) {
#pragma unroll
  for (int i = 0; i < N; i += 4)
    asm volatile("{.reg .pred p; setp.ne.u32 p, %4, 0; @p st.shared.v4.u32 [%4], {%0,%1,%2,%3};}"
                 ::"r"(as_u(d[i])), "r"(as_u(d[i + 1 < N ? i + 1 : i])), "r"(as_u(d[i + 2 < N ? i + 2 : i])), "r"(as_u(d[i + 3 < N ? i + 3 : i])), "r"(never) : "memory");
}
template <class T, int N> __device__ __forceinline__ void keep(const T (&d)[N], uint32_t never) { keep<T, N>(&d[0], never); }
template <class T, int M, int N> __device__ __forceinline__ void keep(const T (&d)[M][N], uint32_t never) { keep<T, M * N>(&d[0][0], never); }
__device__ __forceinline__ void keep_ptr(const void* a, const void* b, uint32_t never) {
  asm volatile("{.reg .pred p; setp.ne.u32 p, %2, 0; @p st.shared.v2.u64 [%2], {%0,%1};}" ::"l"(a), "l"(b), "r"(never) : "memory");
}
__device__ __forceinline__ float rsqrt_fast(float x) {
  float r;
  asm("rsqrt.approx.ftz.f32 %0, %1;" : "=f"(r) : "f"(x));
  return r;
}
__device__ __forceinline__ void fence_async_smem() { asm volatile("fence.proxy.async.shared::cta;" ::: "memory"); }
template <int ID, int N> __device__ __forceinline__ void bar_sync() { asm volatile("bar.sync %0, %1;" ::"n"(ID), "n"(N) : "memory"); }
template <int ID, int N> __device__ __forceinline__ void bar_arrive() { asm volatile("bar.arrive %0, %1;" ::"n"(ID), "n"(N) : "memory"); }
__device__ __forceinline__ void bar_wg(int v) { asm volatile("bar.sync %0, 128;" ::"r"(2 + v) : "memory"); }
__device__ __forceinline__ uint32_t desc_lo(uint32_t addr, uint32_t lbo) { return ((addr & 0x3FFFF) >> 4) | ((lbo >> 4) << 16); }
template <uint32_t HI> __device__ __forceinline__ uint64_t desc(uint32_t lo) { return ((uint64_t)HI << 32) | lo; }
constexpr uint32_t HI_DFT = TS >> 4, HI_FIN = 128 >> 4, HI_W = (1024 >> 4) | (1u << 30);
__device__ __forceinline__ void mbar_init(uint32_t b, int c) { asm volatile("mbarrier.init.shared::cta.b64 [%0], %1;" ::"r"(b), "r"(c) : "memory"); }
__device__ __forceinline__ void mbar_arrive(uint32_t b) { asm volatile("mbarrier.arrive.shared::cta.b64 _, [%0];" ::"r"(b) : "memory"); }
__device__ __forceinline__ void mbar_wait(uint32_t b, uint32_t ph) {
  asm volatile("{\n.reg .pred p;\n.reg .u32 c;\nmov.u32 c, 0;\n"
               "LW: mbarrier.try_wait.parity.shared::cta.b64 p, [%0], %1;\n@p bra DW;\n"
               "add.u32 c, c, 1;\nsetp.lt.u32 p, c, %2;\n@p bra LW;\nDW:\n}"
               ::"r"(b), "r"(ph), "n"(SPIN_LIMIT) : "memory");
}
__device__ __forceinline__ void tma_pair(uint32_t bar, int bytes, uint32_t d0, const CUtensorMap* m0, int x0, int y0, uint32_t d1,
                                         const CUtensorMap* m1, int x1, int y1) {
  asm volatile("{\n.reg .pred p;\nelect.sync _|p, 0xffffffff;\n"
               "@p mbarrier.arrive.expect_tx.shared::cta.b64 _, [%0], %1;\n"
               "@p cp.async.bulk.tensor.2d.shared::cluster.global.mbarrier::complete_tx::bytes [%2], [%3, {%4, %5}], [%0];\n"
               "@p cp.async.bulk.tensor.2d.shared::cluster.global.mbarrier::complete_tx::bytes [%6], [%7, {%8, %9}], [%0];\n}"
               ::"r"(bar), "r"(bytes), "r"(d0), "l"(m0), "r"(x0), "r"(y0), "r"(d1), "l"(m1), "r"(x1), "r"(y1) : "memory");
}
__device__ __forceinline__ uint32_t pack2(float lo, float hi) {
  uint32_t r;
  asm("cvt.rn.bf16x2.f32 %0, %1, %2;" : "=r"(r) : "f"(hi), "f"(lo));
  return r;
}
__device__ __forceinline__ float lo2f(uint32_t v) { return __uint_as_float(v << 16); }
__device__ __forceinline__ float hi2f(uint32_t v) { return __uint_as_float(v & 0xFFFF0000u); }
__device__ __forceinline__ float bfround(float v) { return lo2f(pack2(v, 0.f)); }
constexpr float TURN = 6.283185307179586f;
__device__ __forceinline__ int idxq(int q, int k) { return ((q & 1) ? 63 - k : k) + 64 * (q >> 1); }
__device__ __forceinline__ uint32_t rho(int n) { return (n & 1) * ODD + (n >> 1) * 16; }
__device__ __forceinline__ int wcol(int b) {
  const int vs = b >> 4, e = b & 15;
  if (vs == 8) return 256;
  if (vs == 0) return (e >> 3) * 8 * 257 + 32 * (e & 7);
  return e < 8 ? vs * 257 + 32 * e : (16 - vs) * 257 + 481 - 32 * e;
}
__device__ __forceinline__ int wcol2(int b) {
  const int vs = b >> 4, e = b & 15;
  if (vs == 8) return 8 * 257 + 256;
  if (vs == 0 || (e & 7)) return -1;
  return e ? vs * 257 + 256 : (16 - vs) * 257;
}
__device__ __forceinline__ uint32_t tag_of(uint32_t st) { return (st & 1) | ((st & 2) << 15); }
__device__ __forceinline__ uint4 ld_x(const void* p) {
  uint4 v;
  asm volatile("ld.relaxed.gpu.global.v4.u32 {%0,%1,%2,%3}, [%4];" : "=r"(v.x), "=r"(v.y), "=r"(v.z), "=r"(v.w) : "l"(p) : "memory");
  return v;
}
__device__ __forceinline__ void ld_x_into(uint4& v, const void* p) {
  asm volatile("ld.relaxed.gpu.global.v4.u32 {%0,%1,%2,%3}, [%4];" : "+r"(v.x), "+r"(v.y), "+r"(v.z), "+r"(v.w) : "l"(p) : "memory");
}
__device__ __forceinline__ void st_x(void* p, uint32_t tag, uint32_t x, uint32_t y, uint32_t z, uint32_t w) {
  asm volatile("st.relaxed.gpu.global.v4.u32 [%0], {%1,%2,%3,%4};" ::"l"(p), "r"((x & ~TAGM) | tag), "r"(y), "r"(z), "r"(w) : "memory");
}
__device__ __forceinline__ void st_raw(void* p, const uint4& v) {
  asm volatile("st.relaxed.gpu.global.v4.u32 [%0], {%1,%2,%3,%4};" ::"l"(p), "r"(v.x), "r"(v.y), "r"(v.z), "r"(v.w) : "memory");
}
__device__ __forceinline__ void copy_into(uint4& d, const uint4& s, uint32_t zero) {
  asm volatile("and.b32 %0, %4, 0xFFFEFFFE;\nxor.b32 %1, %5, %8;\nxor.b32 %2, %6, %8;\nxor.b32 %3, %7, %8;"
               : "+r"(d.x), "+r"(d.y), "+r"(d.z), "+r"(d.w) : "r"(s.x), "r"(s.y), "r"(s.z), "r"(s.w), "r"(zero));
}
__device__ __forceinline__ uint4* at(const uint4* base, uint32_t off) {
  uint4* r;
  asm volatile("mad.wide.u32 %0, %2, 16, %1;" : "=l"(r) : "l"(base), "r"(off));
  return r;
}
__device__ __forceinline__ uint32_t ld_rlx(const void* p) {
  uint32_t v;
  asm volatile("ld.relaxed.gpu.global.u32 %0, [%1];" : "=r"(v) : "l"(p) : "memory");
  return v;
}
__device__ __forceinline__ void st_rlx(void* p, uint32_t v) { asm volatile("st.relaxed.gpu.global.u32 [%0], %1;" ::"l"(p), "r"(v) : "memory"); }
__device__ __forceinline__ void st_g4(void* p, uint32_t a, uint32_t b, uint32_t c, uint32_t d) {
  asm volatile("st.global.v4.u32 [%0], {%1,%2,%3,%4};" ::"l"(p), "r"(a), "r"(b), "r"(c), "r"(d) : "memory");
}
__device__ __forceinline__ void sts4(uint32_t a, uint32_t x, uint32_t y, uint32_t z, uint32_t w) {
  asm volatile("st.shared.v4.u32 [%0], {%1,%2,%3,%4};" ::"r"(a), "r"(x), "r"(y), "r"(z), "r"(w) : "memory");
}
__device__ __forceinline__ void sts1(uint32_t a, uint32_t x) { asm volatile("st.shared.u32 [%0], %1;" ::"r"(a), "r"(x) : "memory"); }
__device__ __forceinline__ uint4 lds4(uint32_t a) {
  uint4 v;
  asm volatile("ld.shared.v4.u32 {%0,%1,%2,%3}, [%4];" : "=r"(v.x), "=r"(v.y), "=r"(v.z), "=r"(v.w) : "r"(a) : "memory");
  return v;
}
__device__ __forceinline__ void ldsm4(uint32_t (&r)[4], uint32_t a) {
  asm volatile("ldmatrix.sync.aligned.m8n8.x4.shared.b16 {%0,%1,%2,%3}, [%4];" : "=r"(r[0]), "=r"(r[1]), "=r"(r[2]), "=r"(r[3]) : "r"(a) : "memory");
}
__device__ __forceinline__ void ldsm4t(uint32_t (&r)[4], uint32_t a) {
  asm volatile("ldmatrix.sync.aligned.m8n8.x4.trans.shared.b16 {%0,%1,%2,%3}, [%4];" : "=r"(r[0]), "=r"(r[1]), "=r"(r[2]), "=r"(r[3]) : "r"(a) : "memory");
}
__device__ __forceinline__ void stsm4(uint32_t a, uint32_t x, uint32_t y, uint32_t z, uint32_t w) {
  asm volatile("stmatrix.sync.aligned.m8n8.x4.shared.b16 [%0], {%1,%2,%3,%4};" ::"r"(a), "r"(x), "r"(y), "r"(z), "r"(w) : "memory");
}
__device__ __forceinline__ void mma16816(float (&d)[4], const uint32_t (&a)[4], uint32_t b0, uint32_t b1) {
  asm volatile("mma.sync.aligned.m16n8k16.row.col.f32.bf16.bf16.f32 {%0,%1,%2,%3}, {%4,%5,%6,%7}, {%8,%9}, {%10,%10,%10,%10};"
               : "=f"(d[0]), "=f"(d[1]), "=f"(d[2]), "=f"(d[3])
               : "r"(a[0]), "r"(a[1]), "r"(a[2]), "r"(a[3]), "r"(b0), "r"(b1), "f"(0.f));
}
__device__ __forceinline__ float4 lds4f(uint32_t a) {
  float4 v;
  asm volatile("ld.shared.v4.f32 {%0,%1,%2,%3}, [%4];" : "=f"(v.x), "=f"(v.y), "=f"(v.z), "=f"(v.w) : "r"(a) : "memory");
  return v;
}
__device__ __forceinline__ void sts2(uint32_t a, uint32_t x, uint32_t y) { asm volatile("st.shared.v2.u32 [%0], {%1,%2};" ::"r"(a), "r"(x), "r"(y) : "memory"); }
static_assert(TS == 2160 && ES == 1032 && TAGM == 65537 && SPIN_LIMIT == 131072, "baked into the settle loops");

template <int NT> struct Acc { float e[NT * 4], o[NT * 4]; };
template <int NT> __device__ __forceinline__ void dft128(Acc<NT>& a, const uint32_t (&cs)[8][4], uint32_t tile) {
  const uint32_t lo = desc_lo(tile, 128);
  wg_fence();
#pragma unroll
  for (int j = 0; j < 8; j++) {
    const uint64_t db = desc<HI_DFT>(lo + (j >> 2) * (ODD >> 4) + (j & 3) * 16);
    if constexpr (NT == 5) wgmma_rs_n40_tb1(j < 4 ? a.e : a.o, cs[j][0], cs[j][1], cs[j][2], cs[j][3], db, j & 3);
    else wgmma_rs_n32_tb1(j < 4 ? a.e : a.o, cs[j][0], cs[j][1], cs[j][2], cs[j][3], db, j & 3);
  }
  wg_commit();
}
template <int NT> __device__ __forceinline__ void dft_wait(Acc<NT>& a) {
  wg_wait<0>();
  pin(a.e);
  pin(a.o);
}
template <bool INV, int NT> __device__ __forceinline__ void combine(const Acc<NT>& a, int j, float (&re)[4], float (&im)[4]) {
  const float per = a.e[4 * j], pei = a.e[4 * j + 1], qer = a.e[4 * j + 2], qei = a.e[4 * j + 3];
  const float por = a.o[4 * j], poi = a.o[4 * j + 1], qor = a.o[4 * j + 2], qoi = a.o[4 * j + 3];
  const float ar = per + por, ai = pei + poi, br = qer + qor, bi = qei + qoi;
  const float cr = per - por, ci = pei - poi, dr = qer - qor, di = qei - qoi;
  constexpr int A = INV ? 3 : 0, B = INV ? 0 : 3, C = INV ? 1 : 2, D = INV ? 2 : 1;
  re[A] = ar + bi; im[A] = ai - br;
  re[B] = ar - bi; im[B] = ai + br;
  re[C] = cr + di; im[C] = ci - dr;
  re[D] = cr - di; im[D] = ci + dr;
}
template <int NT> __device__ __forceinline__ void combine_s(const Acc<NT>& a, int j, float al, float be, uint32_t (&pk)[4]) {
  const float per = a.e[4 * j], pei = a.e[4 * j + 1], qer = a.e[4 * j + 2], qei = a.e[4 * j + 3];
  const float por = a.o[4 * j], poi = a.o[4 * j + 1], qor = a.o[4 * j + 2], qoi = a.o[4 * j + 3];
  const float ar = fmaf(al, por, per), ai = fmaf(al, poi, pei), br = fmaf(al, qor, qer), bi = fmaf(al, qoi, qei);
  const float cr = fmaf(-al, por, per), ci = fmaf(-al, poi, pei), dr = fmaf(-al, qor, qer), di = fmaf(-al, qoi, qei);
  pk[0] = pack2(fmaf(-be, bi, ar), fmaf(be, br, ai));
  pk[1] = pack2(fmaf(be, bi, ar), fmaf(-be, br, ai));
  pk[2] = pack2(fmaf(-be, di, cr), fmaf(be, dr, ci));
  pk[3] = pack2(fmaf(be, di, cr), fmaf(-be, dr, ci));
}
__device__ __forceinline__ void mma_acc(float (&d)[4], const uint32_t (&a)[4], uint32_t b0, uint32_t b1) {
  asm volatile("mma.sync.aligned.m16n8k16.row.col.f32.bf16.bf16.f32 {%0,%1,%2,%3}, {%4,%5,%6,%7}, {%8,%9}, {%0,%1,%2,%3};"
               : "+f"(d[0]), "+f"(d[1]), "+f"(d[2]), "+f"(d[3]) : "r"(a[0]), "r"(a[1]), "r"(a[2]), "r"(a[3]), "r"(b0), "r"(b1));
}
__device__ __forceinline__ uint32_t hfma2(uint32_t a, uint32_t b, uint32_t c) {
  uint32_t r;
  asm("fma.rn.bf16x2 %0, %1, %2, %3;" : "=r"(r) : "r"(a), "r"(b), "r"(c));
  return r;
}
__device__ __forceinline__ uint32_t lds1(uint32_t a) {
  uint32_t v;
  asm volatile("ld.shared.u32 %0, [%1];" : "=r"(v) : "r"(a) : "memory");
  return v;
}
__device__ __forceinline__ float lds_bf16(uint32_t a) {
  uint32_t v;
  asm volatile("ld.shared.u16 %0, [%1];" : "=r"(v) : "r"(a) : "memory");
  return lo2f(v);
}
__device__ __forceinline__ uint32_t now() { uint32_t c; asm volatile("mov.u32 %0, %%clock;" : "=r"(c)::"memory"); return c; }
__device__ __forceinline__ void pause_since(uint32_t t0, uint32_t clks) {
  while (now() - t0 < clks) {}
}
__device__ __forceinline__ void cp16(uint32_t dst, const void* src) {
  asm volatile("cp.async.cg.shared.global.L2::128B [%0], [%1], 16;" ::"r"(dst), "l"(src) : "memory");
}
__device__ __forceinline__ uint32_t cmul_pack(float r, float i, float c, float s) { return pack2(r * c - i * s, r * s + i * c); }
__device__ __forceinline__ void silu_pre(float& h, float& u) { asm volatile("mul.f32 %1, %0, %1;\ntanh.approx.f32 %0, %0;" : "+f"(h), "+f"(u)); }
__device__ __forceinline__ uint32_t silu_post(const float* th, const float* hu) { return pack2(fmaf(hu[0], th[0], hu[0]), fmaf(hu[1], th[1], hu[1])); }

constexpr uint32_t XDELAY = 1400;
constexpr uint32_t MDELAY = 400;
constexpr uint32_t GDELAY = 1180;
constexpr uint32_t GSKEW = 300;
constexpr uint32_t LEAD = 200;
constexpr uint32_t M2DELAY = 300;
constexpr uint32_t ZDELAY = 1000;
constexpr uint32_t M3DELAY = 500;
constexpr uint32_t NSKEW = 500;
constexpr uint32_t HDELAY = 1050;
constexpr uint32_t HSKEW = 400;
constexpr int NPRE = 7;
constexpr int LAG = 5, LAG2 = 4;
static_assert(NPRE <= NEARLY + 2, "slots released early must not alias live FFT scratch");
static_assert(16 - NSLOT >= LAG, "the ring keeps warpgroup 0 from arriving twice on the stagger barrier");

#define TAG_G tag_of(3 * ep0 + 1)
#define TAG_Z tag_of(3 * ep0 + 2)
#define TAG_H2 tag_of(3 * ep0 + 3)
#define TAG_E tag_of(ep0 + 1)
#define TAG_H0 tag_of(2 * ep0 + 1)
#define TAG_P tag_of(2 * ep0 + 2)

struct Maps { CUtensorMap m[6]; };

__global__ void __launch_bounds__(384, 1)
fused_kernel(const __nv_bfloat16* __restrict__ wmod, const __nv_bfloat16* __restrict__ cvec, Scratch* __restrict__ scratch,
             const __nv_bfloat16* __restrict__ x, const __nv_bfloat16* __restrict__ wr, const __nv_bfloat16* __restrict__ wi,
             __nv_bfloat16* __restrict__ out, const __grid_constant__ Maps maps) {
  extern __shared__ __align__(1024) unsigned char smem[];
  constexpr uint32_t sb = SB;
  const int tid = threadIdx.x, lane = tid & 31, b = blockIdx.x;
  const uint32_t never = threadIdx.y;
  Scratch& S = *scratch;
  const uint32_t bar_full = sb + OFF_BAR, bar_empty = bar_full + NSLOT * 8, bar_w = bar_empty + NSLOT * 8, bar_m = bar_w + 8, bar_x = bar_m + 8;
  const bool main_cta = b < 128;
  const int vs = b >> 4;

  if (tid >= 256) {
    asm volatile("setmaxnreg.dec.sync.aligned.u32 88;");
    {
      const uint32_t l16 = (tid & 96) * 8 + lane * 16, row = 4 * (tid & 96) + lane;
      const char* src = (const char*)wmod + (row * 6144 + 16 * b);
      asm volatile("{\n.reg .pred p, q;\nsetp.lt.u32 p, %0, 16;\nsetp.eq.u32 q, %0, 16;\n"
                   "@p cp.async.cg.shared.global [%1], [%2], 16;\n@q cp.async.cg.shared.global [%3], [%4], 16;\ncp.async.commit_group;\n}"
                   ::"r"(lane), "r"(sb + OFF_STAT + l16), "l"((const char*)cvec + l16), "r"(sb + OFF_EP + (tid & 96) / 2), "l"(&S.epoch[b * 8]) : "memory");
#pragma unroll
      for (int r = 0; r < 4; r++) {
        const uint32_t rr = (r + b) & 3;
        cp16(sb + OFF_Y + row * 16 + rr * 512, src + rr * (32 * 6144));
      }
      asm volatile("cp.async.commit_group;" ::: "memory");
    }
    if (s2u(smem) != SB) __trap();
    const int wc1 = wcol(b), wc2 = wcol2(b);
    const int i = tid - 256, w = __shfl_sync(0xffffffffu, i >> 5, 0), p = b & 7;
    if (i == 0) {
#pragma unroll
      for (int s = 0; s < NSLOT; s++) { mbar_init(bar_full + s * 8, 1); mbar_init(bar_empty + s * 8, 8); }
      mbar_init(bar_w, 129);
      mbar_init(bar_m, 2);
      asm volatile("fence.mbarrier_init.release.cluster;" ::: "memory");
    }
    if (i >= 32 && i < 38) asm volatile("prefetch.tensormap [%0];" ::"l"(&maps.m[i - 32]) : "memory");
    if (i < 8) sts1(sb + OFF_MA + 128 * 48 + 4 * i, 0u);
    uint32_t* mw = &S.M[(i >> 4) * 3072 + (i & 15)];
    if (main_cta) {
      if (!(i & 8)) st_rlx(mw + 8 * b, 0u);
      st_rlx(mw + 1024 + 16 * b, 0u);
    }
    const uint32_t* mc = &S.M[(vs & 7) * 3072];
    const float zr = 16.f * __cosf(b * (TURN / 256)), zi = 16.f * __sinf(b * (TURN / 256));
    uint32_t sc[8];
    asm volatile("cp.async.wait_group 1;" ::: "memory");
    __syncwarp();
    const uint32_t mtag = (lds1(sb + OFF_EP + (i >> 5) * 16) & 0x7FFF) | 0x8000;
    {
      uint2 cr;
      asm volatile("ld.shared.v2.u32 {%0,%1}, [%2];" : "=r"(cr.x), "=r"(cr.y) : "r"(sb + OFF_STAT + i * 8) : "memory");
      const float c0 = lo2f(cr.x), c1 = hi2f(cr.x), c2 = lo2f(cr.y), c3 = hi2f(cr.y);
      sts2(sb + OFF_STAT + i * 8, pack2(__fdividef(c0, 1.f + __expf(-c0)), __fdividef(c1, 1.f + __expf(-c1))),
           pack2(__fdividef(c2, 1.f + __expf(-c2)), __fdividef(c3, 1.f + __expf(-c3))));
      bar_sync<6, 128>();
#pragma unroll
      for (int e = 0; e < 8; e++) sc[e] = lds1(sb + OFF_STAT + w * 256 + e * 32 + (lane & 7) * 4);
    }
    auto load_w = [&]() {
      if (w == 0) tma_pair(bar_w, 20480, sb + OFF_W, &maps.m[3], wc1 & ~7, 0, sb + OFF_W + 10240, &maps.m[4], wc1 & ~7, 0);
      if (wc2 >= 0) {
        const int o = (vs == 8 ? i : 127 - i) * 4112 + (wc2 & ~7);
        cp16(sb + OFF_W + 20480 + i * 16, wr + o);
        cp16(sb + OFF_W + 22528 + i * 16, wi + o);
      }
      asm volatile("cp.async.mbarrier.arrive.noinc.shared::cta.b64 [%0];" ::"r"(bar_w) : "memory");
    };
    auto gemv8 = [&](uint32_t src, uint32_t pitch, uint32_t red) {
      float d[2][4] = {{0.f, 0.f, 0.f, 0.f}, {0.f, 0.f, 0.f, 0.f}};
#pragma unroll
      for (int jj = 0; jj < 4; jj++) {
        uint32_t am[4];
        ldsm4t(am, src + (128 * w + 32 * jj + lane) * pitch);
        mma_acc(d[jj & 1], am, sc[2 * jj], sc[2 * jj + 1]);
      }
      if ((lane & 3) == 0) sts1(red + lane * 4 + w * 4, __float_as_uint((d[0][0] + d[0][3]) + (d[1][0] + d[1][3])));
    };
    auto publish = [&](uint32_t red, int col0) {
      const float4 q = lds4f(red + (i & 15) * 16);
      float mm = bfround((q.x + q.y) + (q.z + q.w));
      if ((col0 >> 9) == 1 || (col0 >> 9) == 4) mm = bfround(1.f + mm);
      if (col0 >= 1536) mm *= col0 < 2560 ? 0.5f : 2.f;
      st_rlx(mw + col0, (__float_as_uint(mm) & 0xFFFF0000u) | mtag);
    };
    auto issue_stage = [&](int n, int slot) {
      const uint32_t dst = sb + slot * SLOT, fb = bar_full + slot * 8;
      const CUtensorMap *ma, *mb;
      int xa0, xb0, ya, yb;
      if (n < 24) {
        ma = &maps.m[0]; mb = &maps.m[1];
        xa0 = xb0 = 176 * p + 64 * (n >> 3);
        ya = yb = 128 * (n & 3) + 16 * (n & 4);
      } else {
        const int m = n - 24, sl = p + (m < 4 ? 2 * m : 4 * (m & 1)), r0 = m < 4 ? 0 : 64 + 32 * (m & 2);
        ma = mb = &maps.m[2];
        xa0 = 64 * (m < 8 ? p ^ 1 : p);
        xb0 = m < 4 ? 64 * p : xa0;
        ya = 176 * (sl & 7) + r0;
        yb = m < 4 ? ya : 176 * ((sl + 2) & 7) + r0;
      }
      tma_pair(fb, SLOT, dst, ma, xa0, ya, dst + 8192, mb, xb0, yb);
    };
    { const uint32_t kp[4] = {mtag, __float_as_uint(zr), __float_as_uint(zi), (uint32_t)(uintptr_t)(mw + 8 * b)}; keep(kp, never); }
    asm volatile("cp.async.wait_group %0;" ::"n"(0) : "memory");
    __syncwarp();
    gemv8(sb + OFF_Y, 16, sb + OFF_RED);
    bar_sync<6, 128>();
    if (!(i & 8) && main_cta) publish(sb + OFF_RED, 8 * b);
    pause_since(now(), MDELAY);
    {
      uint32_t m[8];
#pragma unroll 1
      for (int it = 0; it < SPIN_LIMIT; it++) {
        uint32_t bad = 0;
#pragma unroll
        for (int e = 0; e < 8; e++) m[e] = ld_rlx(mc + 128 * e + i);
        if (it == 0) { pause_since(now(), 1); load_w(); }
#pragma unroll
        for (int e = 0; e < 8; e++) { m[e] ^= mtag; bad |= m[e]; }
        const float s0 = __uint_as_float(m[0]), s1 = __uint_as_float(m[1]), s2 = __uint_as_float(m[2]), s3 = __uint_as_float(m[3]);
        const float e0 = s0 + s2, e1 = s0 - s2, e2 = s1 + s3, e3 = s1 - s3;
        const uint32_t dst = sb + OFF_MA + i * 48;
        sts4(dst, m[4], m[5], m[6], m[7]);
        sts4(dst + 16, __float_as_uint(e0 * zr), __float_as_uint(e1 * zr), __float_as_uint(e2 * zr), __float_as_uint(e3 * zr));
        sts4(dst + 32, __float_as_uint(e0 * zi), __float_as_uint(e1 * zi), __float_as_uint(e2 * zi), __float_as_uint(e3 * zi));
        if (!__any_sync(0xffffffffu, bad << 16)) break;
      }
    }
    bar_arrive<5, 384>();
    if (!main_cta) {
      asm volatile("cp.async.wait_all;" ::: "memory");
      return;
    }
    if (w == 0) issue_stage(0, 0);
    mbar_wait(bar_empty, 0);
    pause_since(now(), M2DELAY);
    if (w == 0) tma_pair(bar_m, SLOT / 2, sb + OFF_WM, &maps.m[5], 1024 + 16 * b, 0, sb + OFF_WM + 4096, &maps.m[5], 1024 + 16 * b, 128);
    if (w == 0) tma_pair(bar_m, SLOT / 2, sb + OFF_WM + 8192, &maps.m[5], 1024 + 16 * b, 256, sb + OFF_WM + 12288, &maps.m[5], 1024 + 16 * b, 384);
    auto gather = [&](const uint32_t* gp, uint32_t dst, int n, bool packed) {
      uint4 q[4];
#pragma unroll 1
      for (int it = 0; it < SPIN_LIMIT; it++) {
        uint32_t bad = 0;
#pragma unroll
        for (int a = 0; a < n; a++) q[a] = ld_x(gp + 4 * lane + 128 * a);
#pragma unroll
        for (int a = 0; a < n; a++) { q[a].x ^= mtag; q[a].y ^= mtag; q[a].z ^= mtag; q[a].w ^= mtag; bad |= q[a].x | q[a].y | q[a].z | q[a].w; }
        if (!__any_sync(0xffffffffu, bad & 0xFFFF)) break;
      }
      if (packed) {
        dst += (lane >> 3) * 64 + (lane & 1) * 32 + (lane & 6) * 2;
#pragma unroll
        for (int a = 0; a < n; a++) { sts1(dst + a * 256, __byte_perm(q[a].x, q[a].y, 0x7632)); sts1(dst + a * 256 + 16, __byte_perm(q[a].z, q[a].w, 0x7632)); }
      } else {
        dst += (lane >> 2) * 64 + (lane & 1) * 32 + (lane & 2) * 4;
#pragma unroll
        for (int a = 0; a < n; a++) { sts2(dst + a * 512, q[a].x, q[a].y); sts2(dst + a * 512 + 16, q[a].z, q[a].w); }
      }
    };
    mbar_wait(bar_m, 0);
    gemv8(sb + OFF_WM, 32, sb + OFF_RED + 128);
    gemv8(sb + OFF_WM + 16, 32, sb + OFF_RED + 256);
    bar_sync<6, 128>();
    publish(sb + OFF_RED + 128, 1024 + 16 * b);
    mbar_wait(bar_empty + (w ? 8 : 16), 0);
    if (w > 0) {
      pause_since(now(), M3DELAY);
      gather(mc + 512 + 512 * w, sb + OFF_XRAW - 2048 + w * 2048, 4, w > 1);
      bar_arrive<12, 224>();
      bar_arrive<13, 224>();
    } else {
#pragma unroll 1
      for (int n = 1; n < NPRE; n++) { mbar_wait(bar_empty + n * 8, 0); issue_stage(n, n); }
    }
    asm volatile("setmaxnreg.dec.sync.aligned.u32 24;");
    if (w == 1) {
      gather(mc + 2560 + 64 * (p & ~1), sb + OFF_GB, 1, false);
      bar_arrive<8, 160>();
      bar_arrive<9, 160>();
    }
    if (!(w & 1)) {
      int slot = NPRE + (w >> 1);
      uint32_t ph = 0;
#pragma unroll 1
      for (int n = slot; n < NSTAGE; n += 2) {
        mbar_wait(bar_empty + slot * 8, ph);
        issue_stage(n, slot);
        slot += 2;
        if (slot >= NSLOT) { slot -= NSLOT; ph ^= 1; }
      }
    }
  } else {
    asm volatile("setmaxnreg.inc.sync.aligned.u32 208;");
    const uint32_t tstart = now();
    const int wu = __shfl_sync(0xffffffffu, tid >> 5, 0), v = wu >> 2;
    const int w = (tid >> 5) & 3, wq = tid >> 5, g = lane >> 2, t = lane & 3, i = tid & 127;
    const uint32_t RX = sb + OFF_X, RY = sb + OFF_Y;
    uint4 xv[4];
    uint32_t ep0;
    asm volatile("{\n.reg .pred p;\nelect.sync _|p, 0xffffffff;\n@p mbarrier.init.shared::cta.b64 [%0], 1;\n"
                 "@p mbarrier.arrive.expect_tx.shared::cta.b64 _, [%0], 2048;\nfence.proxy.async.shared::cta;\n}" ::"r"(bar_x + wu * 8) : "memory");
    __syncwarp();
    const int k = 8 * w + g;
    const int grp = 2 * (b & 15) + v, tile = (vs * 32 + grp) * 4;
    const int tcol = t ^ (vs ? (grp >> 3) & 2 : ((grp >> 2) ^ (grp >> 3)) & 2);
    const int bkd1 = vs == 8 ? 64 : 4 * (vs ? grp : grp & 15) + tcol;

    uint32_t cs[8][4];
    {
      const float kk = (2 * k + 1) * (TURN / 256), k4 = kk * (4 * t);
      const uint32_t mo = (k & 1) ? 0x80008000u : 0u, me = mo ^ 0x80008000u;
#pragma unroll
      for (int n = 0; n < 8; n++) {
        const int pp = n >> 2, jj = (n >> 1) & 1, h = n & 1, n0 = 32 * jj + 16 * h + pp;
        const float a0 = fmaf(kk, n0, k4), a1 = fmaf(kk, n0 + 2, k4);
        const uint32_t C = pack2(__cosf(a0), __cosf(a1)), Sn = pack2(__sinf(a0), __sinf(a1));
        cs[4 * pp + jj][2 * h] = C;           cs[4 * pp + jj][2 * h + 1] = Sn;
        cs[4 * pp + jj + 2][2 * h] = Sn ^ me; cs[4 * pp + jj + 2][2 * h + 1] = C ^ mo;
      }
    }
    keep(cs, never);
    pause_since(tstart, XDELAY);
    asm volatile("{\n.reg .pred p;\nelect.sync _|p, 0xffffffff;\n"
                 "@p cp.async.bulk.shared::cluster.global.mbarrier::complete_tx::bytes [%0], [%1], 1024, [%2];\n"
                 "@p cp.async.bulk.shared::cluster.global.mbarrier::complete_tx::bytes [%0 + 1040], [%1 + 131072], 1024, [%2];\n}"
                 ::"r"(sb + OFF_XRAW + wu * 2 * XS), "l"(x + (size_t)(256 * wu + (b & 127)) * 512), "r"(bar_x + wu * 8) : "memory");
    uint32_t xa[4][4];

    {
      uint32_t f1[2][2], f8[4];
#pragma unroll
      for (int n = 0; n < 2; n++) {
        const float ks1 = ((g >> 1) + 4 * n) * (TURN / 2048), p0 = fmaf(ks1, 256 * t + b, (64 * (g & 1) - b) * (TURN / 256));
#pragma unroll
        for (int h = 0; h < 2; h++) f1[n][h] = pack2(__cosf(fmaf(ks1, 1024 * h, p0)), __cosf(fmaf(ks1, 1024 * h + 128, p0)));
      }
#pragma unroll
      for (int d0 = 0; d0 < 4; d0++) {
        const int m = (g & 1) + d0 * (g >> 1);
        f8[d0] = (m & 1) ? 0u : ((m & 2) ? 0x3F80BF80u : 0xBF803F80u);
      }
      const int d1 = 64 * v + 16 * w + g;
      float twc[2][3], tws[2][3];
#pragma unroll
      for (int r = 0; r < 2; r++) {
        const float th = (d1 + 8 * r) * (TURN / 512);
#pragma unroll
        for (int q = 0; q < 3; q++) {
          const float a = th * (q < 2 ? q + 1 : 2 - t);
          twc[r][q] = __cosf(a);
          tws[r][q] = __sinf(a);
        }
      }
      keep(f1, never); keep(f8, never); keep(twc, never); keep(tws, never);
      const int ga = g & 3;
      const float al = (ga & 2) ? -1.f : 1.f, be = (ga & 1) ? 1.f : -1.f, al0 = v ? al : -be;
      uint4* gq = &S.E[b * ES + v * 512 + t + (idxq((4 - ga) & 3, k) & ~3)];
      uint4* gq0 = v ? gq : &S.E[b * ES + t + 32 * (ga & 2) + (idxq(ga & 1, k) & ~3)];
      const uint32_t xo = (tid >> 4) * XS + (lane & 15) * 16;
      const uint32_t la = RX + ((lane & 7) + 8 * (lane >> 4)) * XS + (64 * v + 16 * w + (lane & 8)) * 2;
      const uint32_t ma = sb + OFF_MA + d1 * 48, mz0 = t ? sb + OFF_MA + 128 * 48 : ma + 16, mz1 = t ? mz0 : ma + 400;
      const uint32_t row = RY + rho(d1) + t * TS, row8 = RY + rho(d1) + 4 * TS + 4 * t;
      { const uint32_t kp[12] = {xo, la, la, ma, mz0, mz1, row, row8, as_u(al), as_u(be), as_u(al0), xo}; keep(kp, never); }
      keep_ptr(gq, gq0, never);
      keep_ptr(out, out, never);
      mbar_wait(bar_x + wu * 8, 0);
#pragma unroll
      for (int r = 0; r < 4; r++) xv[r] = lds4(sb + OFF_XRAW + xo + 256 * r);
      float su[2][4], q1[2][4], q2[2][4];
#pragma unroll
      for (int r = 0; r < 4; r++) {
        const uint32_t a[4] = {xv[r].x, xv[r].y, xv[r].z, xv[r].w};
        if (r < 2) { mma16816(q1[r & 1], a, a[0], a[2]); mma16816(q2[r & 1], a, a[1], a[3]); mma16816(su[r & 1], a, 0x3F803F80u, 0x3F803F80u); }
        else { mma_acc(q1[r & 1], a, a[0], a[2]); mma_acc(q2[r & 1], a, a[1], a[3]); mma_acc(su[r & 1], a, 0x3F803F80u, 0x3F803F80u); }
      }
      float sum = (su[0][0] + su[0][2]) + (su[1][0] + su[1][2]);
      float sqs = (g & 1) ? (q1[0][1] + q2[0][3]) + (q1[1][1] + q2[1][3]) : (q1[0][0] + q2[0][2]) + (q1[1][0] + q2[1][2]);
      sqs = __shfl_sync(0xffffffffu, sqs, (lane & 28) | (g >> 1));
#pragma unroll
      for (int o = 4; o < 16; o <<= 1) { sum += __shfl_xor_sync(0xffffffffu, sum, o); sqs += __shfl_xor_sync(0xffffffffu, sqs, o); }
      const float mu = sum * (1.f / 512.f);
      const float rs = rsqrt_fast(fmaxf(fmaf(sqs, 1.f / 512.f, fmaf(-mu, mu, 1e-5f)), 1e-5f));
      const uint32_t r2 = pack2(rs, rs);
      const float mr = -mu * lo2f(r2);
      const uint32_t m2 = pack2(mr, mr);
#pragma unroll
      for (int r = 0; r < 4; r++) sts4(RX + xo + 256 * r, hfma2(xv[r].x, r2, m2), hfma2(xv[r].y, r2, m2), hfma2(xv[r].z, r2, m2), hfma2(xv[r].w, r2, m2));
      bar_sync<1, 256>();
      float D[4][3][4];
#pragma unroll
      for (int d0 = 0; d0 < 4; d0++) {
        uint32_t a[4];
        ldsm4t(a, la + 256 * d0);
        mma16816(D[d0][1], a, f1[1][0], f1[1][1]);
        mma16816(D[d0][0], a, f1[0][0], f1[0][1]);
        mma16816(D[d0][2], a, f8[d0], f8[d0]);
      }
      bar_sync<5, 384>();
      ep0 = lds1(sb + OFF_EP + never);
      {
        Acc<5> acc;
#pragma unroll
        for (int n = 1; n >= 0; n--) {
          const float4 mm[2] = {lds4f(ma), lds4f(ma + 384)};
          float4 zz[2][2];
          if (n == 0) { zz[0][0] = lds4f(mz0); zz[0][1] = lds4f(mz0 + 16); zz[1][0] = lds4f(mz1); zz[1][1] = lds4f(mz1 + 16); }
#pragma unroll
          for (int r = 0; r < 2; r++) {
            const float4 m = mm[r];
            float A[2], B[2], C[2], E[2];
#pragma unroll
            for (int c = 0; c < 2; c++) {
              const float u0 = D[0][n][2 * r + c], u1 = D[1][n][2 * r + c], u2 = D[2][n][2 * r + c], u3 = D[3][n][2 * r + c];
              if (n == 0) {
                const float4 z = zz[r][c];
                A[c] = fmaf(u2, m.z, fmaf(u0, m.x, z.x)); B[c] = fmaf(-u2, m.z, fmaf(u0, m.x, z.y));
                C[c] = fmaf(u3, m.w, fmaf(u1, m.y, z.z)); E[c] = fmaf(-u3, m.w, fmaf(u1, m.y, z.w));
              } else {
                const float p0 = u0 * m.x, p1 = u1 * m.y;
                A[c] = fmaf(u2, m.z, p0); B[c] = fmaf(-u2, m.z, p0);
                C[c] = fmaf(u3, m.w, p1); E[c] = fmaf(-u3, m.w, p1);
              }
            }
            sts4(row + r * 64 + 5 * n * TS, cmul_pack(A[0] + C[0], A[1] + C[1], twc[r][1], tws[r][1]),
                 cmul_pack(B[0] + E[1], B[1] - E[0], twc[r][0], tws[r][0]), pack2(A[0] - C[0], A[1] - C[1]),
                 cmul_pack(B[0] - E[1], B[1] + E[0], twc[r][0], -tws[r][0]));
            if (n == 0) {
              const float er = fmaf(D[3][2][2 * r], m.w, fmaf(D[2][2][2 * r], m.z, fmaf(D[1][2][2 * r], m.y, D[0][2][2 * r] * m.x)));
              const float ei = fmaf(D[3][2][2 * r + 1], m.w, fmaf(D[2][2][2 * r + 1], m.z, fmaf(D[1][2][2 * r + 1], m.y, D[0][2][2 * r + 1] * m.x)));
              sts1(row8 + r * 64, cmul_pack(er, ei, twc[r][2], tws[r][2]));
            }
          }
          fence_async_smem();
          if (v == n) {
            if (n) bar_sync<4, 256>(); else bar_sync<1, 256>();
            dft128<5>(acc, cs, SB + OFF_Y + 5 * n * TS);
          } else {
            if (n) bar_arrive<4, 256>(); else bar_arrive<1, 256>();
          }
        }
        dft_wait(acc);
#pragma unroll
        for (int j = 3; j >= 0; j--) {
          uint32_t pk[4];
          combine_s(acc, j, j ? al : al0, be, pk);
          if (j == 0 && v == 0) {
            uint32_t p8[4];
            combine_s(acc, 4, -be, be, p8);
            if (k == 0) st_x(gq0 + 1024, TAG_G, pk[2], p8[2], 0u, 0u);
            const bool sw = ga & 2;
            const uint32_t u0 = pk[0], u3 = pk[3];
            pk[0] = sw ? p8[0] : u0; pk[1] = sw ? p8[3] : u3; pk[2] = sw ? u0 : p8[0]; pk[3] = sw ? u3 : p8[3];
          }
#pragma unroll
          for (int e = 1; e < 4; e++) pk[e] = __shfl_xor_sync(0xffffffffu, pk[e], 4 * e);
          st_x(j ? gq + j * 128 : gq0, TAG_G, pk[0], pk[1], pk[2], pk[3]);
        }
      }
    }
    if (!main_cta && v == 1) return;

    const uint32_t tg = now();
#pragma unroll
    for (int jj = 0; jj < 4; jj++) ldsm4(xa[jj], sb + OFF_XRAW + (lane & 15) * XS + (128 * w + 64 * v + (lane >> 4) * 8) * 2 + 32 * jj);
    const uint4* gp = &S.E[(i >> 2) * ES + tile + (i & 3)];
    uint4 gv[4];
    float wfr[4][4], wfi[4][4];
    const bool mir = vs > 0 && vs < 8 && grp >= 16, edge = (bkd1 & 63) == 0;
    const int wo = vs == 8 ? 0 : 16 * v + 4 * tcol, dj = mir ? -2 : 2;
    const uint32_t wa = sb + OFF_W + ((wcol(b) & 7) + (mir ? 31 - wo : wo)) * 2, wb = sb + OFF_W + 20480 + (wcol2(b) & 7) * 2;
    const float s1 = vs == 8 ? 0.f : 1.f, sA = vs == 8 ? (t == 0 ? 0.5f : 0.f) : (edge ? 0.5f : 1.f);
    const bool use2 = vs == 8 ? t == 1 : (vs > 0 && edge);
    const float sC = vs == 8 ? 0.5f : -0.5f, smir = mir ? -0x1p-19f : 0x1p-19f;
    const int lrow = idxq(lane >> 3, 8 * w + (lane & 7));
    const uint32_t gdst = RX + (5 * v + (i & 3)) * TS + rho(i >> 2), ydst = RY + 5 * v * TS + rho(lrow);
    uint4 *zq = &S.E[k * ES + tile + tcol], *zq1 = &S.E[(63 - k) * ES + tile + tcol];
    { const uint32_t kp[4] = {gdst, ydst, TAG_Z, bar_empty + lane * 8}; keep(kp, never); }
    keep_ptr(zq, zq1, never);
    mbar_wait(bar_w, 0);
#pragma unroll
    for (int q = 0; q < 4; q++) {
      const int row = mir ? 127 - idxq(q, k) : idxq(q, k);
      const uint32_t a = wa + row * 80;
#pragma unroll
      for (int j = 0; j < 4; j++) { wfr[q][j] = lds_bf16(a + j * dj); wfi[q][j] = lds_bf16(a + j * dj + 10240); }
      wfr[q][0] *= sA; wfi[q][0] *= sA;
      if (use2) { wfr[q][0] = fmaf(lds_bf16(wb + row * 16), 0.5f, wfr[q][0]); wfi[q][0] = fmaf(lds_bf16(wb + row * 16 + 2048), sC, wfi[q][0]); }
    }
    pause_since(tg, GDELAY + v * GSKEW - ((b >> 6) & 1) * LEAD);
#pragma unroll
    for (int r = 0; r < 4; r++) gv[r] = ld_x(gp + r * 32 * ES);
    if (lane == 0) mbar_arrive(bar_empty);
    mbar_wait(bar_w, 0);
#pragma unroll
    for (int q = 0; q < 4; q++) {
      const float an = (idxq(q, k) + bkd1) * (-TURN / 256), c = __cosf(an), s = __sinf(an);
      float f[4] = {c * 0x1p-19f, s * 0x1p-19f, c * smir, s * smir};
#pragma unroll
      for (int j = 0; j < 4; j++) {
        const float cr = wfr[q][j], ci = wfi[q][j];
        wfr[q][j] = cr * f[0] - ci * f[3];
        wfi[q][j] = cr * f[1] + ci * f[2];
        if (j == 0) { f[0] *= s1; f[1] *= s1; f[2] *= s1; f[3] *= s1; }
      }
    }
    keep(wfr, never); keep(wfi, never);
    mbar_wait(bar_w, 0);
    settle_g(gv, gp, TAG_G, gdst);
    fence_async_smem();
    bar_wg(v);
    {
      Acc<4> acc;
      dft128<4>(acc, cs, SB + OFF_X + 5 * v * TS);
      dft_wait(acc);
#pragma unroll
      for (int j = 0; j < 4; j++) {
        float re[4], im[4];
        combine<false>(acc, j, re, im);
        stsm4(ydst + j * TS, cmul_pack(re[0], im[0], wfr[0][j], wfi[0][j]), cmul_pack(re[1], im[1], wfr[1][j], wfi[1][j]),
              cmul_pack(re[2], im[2], wfr[2][j], wfi[2][j]), cmul_pack(re[3], im[3], wfr[3][j], wfi[3][j]));
      }
      fence_async_smem();
      bar_wg(v);
      dft128<4>(acc, cs, SB + OFF_Y + 5 * v * TS);
      dft_wait(acc);
#pragma unroll
      for (int h = 0; h < 2; h++) {
        uint32_t pa[4], pb[4];
#pragma unroll
        for (int j = 0; j < 4; j++) {
          const float *e = acc.e + 4 * j, *o = acc.o + 4 * j;
          const float ar = h ? e[0] - o[0] : e[0] + o[0], ai = h ? e[1] - o[1] : e[1] + o[1];
          const float br = h ? e[2] - o[2] : e[2] + o[2], bi = h ? e[3] - o[3] : e[3] + o[3];
          pa[j] = pack2(ar - bi, ai + br);
          pb[j] = pack2(ar + bi, ai - br);
        }
        st_x(zq + h * 64 * ES, TAG_Z, pa[0], pa[1], pa[2], pa[3]);
        st_x(zq1 + (1 - h) * 64 * ES, TAG_Z, pb[0], pb[1], pb[2], pb[3]);
      }
    }
    if (!main_cta) {
      if (tid == 0) st_rlx(&S.epoch[b * 8], ep0 + 1);
      return;
    }

    const uint32_t tz = now();
    uint32_t fm[5][4];
    float tc[4], tsn[4];
    {
      const float sa = (128 * g + b) * (TURN / 2048), p0 = (w * t) * (TURN / 4);
#pragma unroll
      for (int n = 0; n < 9; n++) {
        const int ks1 = n < 4 ? n : (n == 4 ? 8 : n - 1);
        const float a = fmaf(sa, ks1, p0);
        const uint32_t e = pack2(__cosf(a), -__sinf(a));
        fm[n >> 1][2 * (n & 1)] = e;
        fm[n >> 1][2 * (n & 1) + 1] = e ^ ((ks1 & 1) ? 0x80008000u : never);
      }
      fm[4][2] = fm[4][3] = 0u;
    }
    keep(fm, never);
    const uint4* zp = &S.E[b * ES + v * 512 + i];
    const bool zextra = (tid & 191) == 0;
    const uint4* zp2 = zextra ? &S.E[b * ES + 1024 + (i >> 6)] : zp;
    const uint32_t zdst = RX + 5 * v * TS + rho(i), zdst0 = v ? zdst : RX + (i >> 6) * 4 * TS + rho(i & 63);
    const uint32_t udst = RY + 5 * v * TS + lrow * 16, mga = sb + OFF_XRAW + (2 * w + v) * 256 + t * 16, mgb = mga + 2048 - (2 * w + v) * 128;
    const uint32_t sta = sb + OFF_STAT + wq * 144 + lane * 4, stb = sb + OFF_STAT + t * 288 + g * 16;
    uint4* hq = &S.E[b * ES + 4 * wq * 32 + lane];
    if (v == 0 && !zextra) sts4(zdst0 + 512, 0u, 0u, 0u, 0u);
    { const uint32_t kp[8] = {zdst, zdst0, udst, mga, sta, stb, TAG_H2, mgb}; keep(kp, never); }
    keep_ptr(zp2, hq, never);
    pause_since(tz, ZDELAY + ((b >> 6) - v) * LEAD);
    uint4 zv[5];
#pragma unroll
    for (int r = 0; r < 5; r++) zv[r] = ld_x(r < 4 ? zp + r * 128 : zp2);
    if (lane == 1) mbar_arrive(bar_empty + 8);
#pragma unroll
    for (int q = 0; q < 4; q++) {
      const float a = (idxq(q, k) * t) * (TURN / 512);
      tc[q] = __cosf(a);
      tsn[q] = __sinf(a);
    }
    keep(tc, never); keep(tsn, never);
    float xf2[32];
#pragma unroll
    for (int e = 0; e < 16; e++) { xf2[2 * e] = lo2f(xa[e >> 2][e & 3]); xf2[2 * e + 1] = hi2f(xa[e >> 2][e & 3]); }
    keep(xf2, never);
    mbar_wait(bar_w, 0);
    settle_z(zv, zp, zp2, TAG_Z, zdst, zdst0);
    if (lane >= 2 && lane < NPRE) mbar_arrive(bar_empty + lane * 8);
    fence_async_smem();
    bar_wg(v);
    {
      Acc<5> acc;
      dft128<5>(acc, cs, SB + OFF_X + 5 * v * TS);
      dft_wait(acc);
#pragma unroll
      for (int j = 0; j < 5; j++) {
        if (j < 4 || v == 0) {
          float re[4], im[4];
          combine<true>(acc, j, re, im);
          stsm4(udst + j * TS, cmul_pack(re[0], im[0], tc[0], tsn[0]), cmul_pack(re[1], im[1], tc[1], tsn[1]),
                cmul_pack(re[2], im[2], tc[2], tsn[2]), cmul_pack(re[3], im[3], tc[3], tsn[3]));
        }
      }
    }
    fence_async_smem();
    bar_sync<1, 256>();
    uint4 hold[4];
    uint32_t th;
    {
      float y[32];
      const uint32_t lo = desc_lo(SB + OFF_Y + 1024 * v, 0);
      wg_fence();
#pragma unroll
      for (int n = 0; n < 5; n++)
        wgmma_rs_n64_tb0(y, fm[n][0], fm[n][1], fm[n][2], fm[n][3], desc<HI_FIN>(lo + n * (2 * TS >> 4) + (n < 4 ? (TS >> 4) << 16 : 0)), n);
      wg_commit();
      asm volatile("bar.sync %0, 224;" ::"r"(12 + v) : "memory");
      float4 mg[4];
      uint4 msb[2], mcb[2];
#pragma unroll
      for (int e = 0; e < 4; e++) mg[e] = lds4f(mga + e * 64);
      wg_wait<0>();
      pin(y);
      float sm[2][2], sq[2][2];
#pragma unroll
      for (int j = 0; j < 8; j++) {
        const float g0 = (j & 1) ? mg[j >> 1].z : mg[j >> 1].x, g1 = (j & 1) ? mg[j >> 1].w : mg[j >> 1].y;
#pragma unroll
        for (int r = 0; r < 2; r++) {
          const float u0 = fmaf(y[4 * j + 2 * r], g0, xf2[4 * j + 2 * r]), u1 = fmaf(y[4 * j + 2 * r + 1], g1, xf2[4 * j + 2 * r + 1]);
          y[4 * j + 2 * r] = u0; y[4 * j + 2 * r + 1] = u1;
          sm[r][0] = j ? sm[r][0] + u0 : u0; sm[r][1] = j ? sm[r][1] + u1 : u1;
          sq[r][0] = j ? fmaf(u0, u0, sq[r][0]) : u0 * u0; sq[r][1] = j ? fmaf(u1, u1, sq[r][1]) : u1 * u1;
        }
      }
      {
        const float a0 = sm[0][0] + sm[0][1], a1 = sq[0][0] + sq[0][1], a2 = sm[1][0] + sm[1][1], a3 = sq[1][0] + sq[1][1];
        const bool h2 = t & 2, h1 = t & 1;
        const float b0 = (h2 ? a2 : a0) + __shfl_xor_sync(0xffffffffu, h2 ? a0 : a2, 2);
        const float b1 = (h2 ? a3 : a1) + __shfl_xor_sync(0xffffffffu, h2 ? a1 : a3, 2);
        const float c0 = (h1 ? b1 : b0) + __shfl_xor_sync(0xffffffffu, h1 ? b0 : b1, 1);
        sts1(sta, __float_as_uint(c0));
      }
      bar_sync<1, 256>();
      th = now();
      if (v) pause_since(th, NSKEW);
      float4 st = lds4f(stb);
      {
        const float4 u = lds4f(stb + 144);
#pragma unroll
        for (int e = 0; e < 2; e++) { mcb[e] = lds4(mgb + 2048 + e * 64); msb[e] = lds4(mgb + e * 64); }
        st.x += u.x; st.y += u.y; st.z += u.z; st.w += u.w;
      }
#pragma unroll
      for (int o = 1; o < 4; o <<= 1) {
        st.x += __shfl_xor_sync(0xffffffffu, st.x, o); st.y += __shfl_xor_sync(0xffffffffu, st.y, o);
        st.z += __shfl_xor_sync(0xffffffffu, st.z, o); st.w += __shfl_xor_sync(0xffffffffu, st.w, o);
      }
      float rs[2], mr[2];
#pragma unroll
      for (int r = 0; r < 2; r++) {
        const float mu = (r ? st.z : st.x) * (1.f / 512.f);
        rs[r] = rsqrt_fast(fmaxf(fmaf(-mu, mu, fmaf(r ? st.w : st.y, 1.f / 512.f, 1e-5f)), 1e-5f));
        mr[r] = -mu * rs[r];
      }
      uint32_t hp[4][4];
#pragma unroll
      for (int jj = 0; jj < 4; jj++) {
#pragma unroll
        for (int e = 0; e < 4; e++) {
          const int r = e & 1;
          const uint4 cq = mcb[jj >> 1], sq4 = msb[jj >> 1];
          const int j = 2 * (jj & 1) + (e >> 1);
          hp[jj][e] = hfma2(pack2(fmaf(y[8 * jj + 2 * e], rs[r], mr[r]), fmaf(y[8 * jj + 2 * e + 1], rs[r], mr[r])),
                        j == 0 ? cq.x : (j == 1 ? cq.y : (j == 2 ? cq.z : cq.w)), j == 0 ? sq4.x : (j == 1 ? sq4.y : (j == 2 ? sq4.z : sq4.w)));
        }
      }
#pragma unroll
      for (int jj = 0; jj < 4; jj++) st_x(hq + jj * 32, TAG_H2, hp[jj][0], hp[jj][1], hp[jj][2], hp[jj][3]);
#pragma unroll
      for (int jj = 0; jj < 4; jj++)
        hold[jj] = make_uint4(pack2(y[8 * jj], y[8 * jj + 1]), pack2(y[8 * jj + 2], y[8 * jj + 3]), pack2(y[8 * jj + 4], y[8 * jj + 5]), pack2(y[8 * jj + 6], y[8 * jj + 7]));
      keep<uint32_t, 16>(&hold[0].x, never);
    }

    asm volatile("setmaxnreg.inc.sync.aligned.u32 240;");
    ep0 = __shfl_sync(0xffffffffu, ep0, 0);
    const int p = b & 7, beta = (b & ~7) + wu;
    const uint4* ap = &S.E[beta * ES + lane];
    uint4 A[32], prev[4];
    pause_since(th, HDELAY + v * HSKEW);
    fetch16_32(A, ap, TAG_H2);
    uint4* hdst = &S.H[(beta * 88 + 11 * p) * 32 + lane];
    const uint32_t wlo = desc_lo(SB, 8192);
#define SLOT_OF(n) ((n) % NSLOT)
#define PHASE_OF(n) (((n) / NSLOT) & 1)
#pragma unroll 1
    for (int c = 0; c < 2; c++) {
      float acc[64];
      const int sa = 8 * c, sw = (8 - NSLOT) * c;
#pragma unroll
      for (int kb2 = 0; kb2 < 8; kb2++) {
        const int slot = kb2 + (kb2 < NSLOT - 8 ? sa : sw);
        mbar_wait(bar_full + slot * 8, kb2 < NSLOT - 8 ? 0 : c);
        if (kb2 == 4 && c == 0) settle16_32(A + 16, ap + 16 * 32, TAG_H2);
        if (kb2 == LAG && v == 1) bar_sync<4, 256>();
        wg_fence();
#pragma unroll
        for (int j = 0; j < 4; j++) {
          const uint4 a = A[4 * kb2 + j];
          wgmma_rs_n128_tb1(acc, a.x, a.y, a.z, a.w, desc<HI_W>(wlo + slot * 1024 + j * 128), kb2 | j);
        }
        wg_commit();
        if (kb2 == 7 && v == 0) bar_arrive<4, 256>();
        if (kb2 == 0 && c == 0) {
#pragma unroll
          for (int n = 16; n < 32; n++) A[n] = ld_x(ap + n * 32);
          if (lane >= NPRE && lane < NSLOT) mbar_arrive(bar_empty + lane * 8);
        }
        if (kb2 == 6 && c == 0) {
          uint4* xd = &S.X1[b * 1024 + (8 * w + 4 * v) * 32 + lane];
#pragma unroll
          for (int jj = 0; jj < 4; jj++) st_x(xd + jj * 32, TAG_E, hold[jj].x, hold[jj].y, hold[jj].z, hold[jj].w);
        }
        if (kb2 > 0) { wg_wait<1>(); if (lane == 0) mbar_arrive(bar_empty + (kb2 - 1 + (kb2 - 1 < NSLOT - 8 ? sa : sw)) * 8); }
      }
      wg_wait<0>();
      pin(acc);
      if (lane == 0) mbar_arrive(bar_empty + (7 + sw) * 8);
#pragma unroll
      for (int e = 0; e < 32; e++) silu_pre(acc[e], acc[32 + e]);
#pragma unroll
      for (int jj = 0; jj < 4; jj++) {
        const float* q = acc + 8 * jj;
        asm volatile("xor.b32 %0, %4, %8;\nxor.b32 %1, %5, %8;\nxor.b32 %2, %6, %8;\nxor.b32 %3, %7, %8;"
                     : "=r"(prev[jj].x), "=r"(prev[jj].y), "=r"(prev[jj].z), "=r"(prev[jj].w)
                     : "r"(hold[jj].x), "r"(hold[jj].y), "r"(hold[jj].z), "r"(hold[jj].w), "r"(blockIdx.y));
        hold[jj] = make_uint4((silu_post(q, q + 32) & ~TAGM) | (c ? TAG_E : TAG_H0), silu_post(q + 2, q + 34), silu_post(q + 4, q + 36), silu_post(q + 6, q + 38));
        st_raw(hdst + jj * 32, hold[jj]);
      }
      hdst += 128;
    }
#define B0(e) A[((e) + 12) & 15]
#define B1(e) A[(e) < 4 ? 28 + (e) : 12 + (e)]
#define B2(e) ((e) < 3 ? own2[(e) % 3] : A[(e) < 3 ? 0 : (e) - 3])
    uint4 own2[3];
    const uint4* xl = &S.X1[lane];
    constexpr uint32_t HO = sizeof(S.X1) / 16;
#define HS(j) at(xl, HO + (beta * 88 + 11 * ((p + 2 * (j)) & 7)) * 32)
#define HS4 {xl, HS(1), HS(2), HS(3)}
#define PP at(xl, HO + (beta * 88 + 11 * (p ^ 1)) * 32)
#define XP at(xl, (beta * 32 + 4 * p) * 32)
    {
      float ag[24], au[24];
#pragma unroll
      for (int kb2 = 0; kb2 < 8; kb2++) {
        const int n = 16 + kb2;
        mbar_wait(bar_full + SLOT_OF(n) * 8, PHASE_OF(n));
        if (kb2 == LAG2 && v == 1) bar_sync<4, 256>();
        wg_fence();
#pragma unroll
        for (int j = 0; j < 4; j++) {
          const uint4 a = A[4 * kb2 + j];
          wgmma_rs_n48_tb1(ag, a.x, a.y, a.z, a.w, desc<HI_W>(wlo + SLOT_OF(n) * 1024 + j * 128), kb2 | j);
          wgmma_rs_n48_tb1(au, a.x, a.y, a.z, a.w, desc<HI_W>(wlo + SLOT_OF(n) * 1024 + 512 + j * 128), kb2 | j);
        }
        wg_commit();
        if (kb2 == 7) { if (v == 0) bar_arrive<4, 256>(); else bar_arrive<10, 256>(); }
        if (kb2 > 0) {
          wg_wait<1>();
          if (lane == 0) mbar_arrive(bar_empty + SLOT_OF(n - 1) * 8);
        }
        if (kb2 == 4) {
#pragma unroll
          for (int e = 0; e < 4; e++) copy_into(B0(e), prev[e], blockIdx.y);
        }
        if (kb2 >= 1 && kb2 <= 3) {
          const uint4* q = HS(kb2);
#pragma unroll
          for (int e = 0; e < 4; e++) ld_x_into(B0(4 * kb2 + e), q + e * 32);
        }
        if (kb2 == 7) {
          mbar_wait(bar_w, 0);
          const uint4* const hs[4] = HS4;
          settle_h0(A, hs, TAG_H0);
#pragma unroll
          for (int e = 4; e < 16; e++) ld_x_into(B1(e), hs[e >> 2] + (4 + (e & 3)) * 32);
        }
      }
      mbar_wait(bar_w, 0);
      wg_wait<0>();
      if (lane == 0 && 23 + NSLOT < NSTAGE) mbar_arrive(bar_empty + SLOT_OF(23) * 8);
      pin(ag);
      pin(au);
#pragma unroll
      for (int e = 0; e < 24; e++) silu_pre(ag[e], au[e]);
#pragma unroll
      for (int jj = 0; jj < 3; jj++) {
        const float *q = ag + 8 * jj, *u = au + 8 * jj;
        own2[jj] = make_uint4(silu_post(q, u) & ~TAGM, silu_post(q + 2, u + 2), silu_post(q + 4, u + 4), silu_post(q + 6, u + 6));
        st_x(hdst + jj * 32, TAG_E, own2[jj].x, own2[jj].y, own2[jj].z, own2[jj].w);
      }
    }
    {
      float acc[32], aco[32];
      float xr[8][4];
      float4 gb[4];
      const uint32_t stg = sb + OFF_XRAW + wq * 2048, sw = stg + (lane & 15) * 128 + (((lane >> 4) ^ (lane & 7)) << 4);
      const uint32_t sr = stg + (lane >> 3) * 128 + (((lane & 7) ^ (lane >> 3)) << 4);
      __nv_bfloat16* op = out + (size_t)(beta + 128 * (lane >> 3)) * 512 + 64 * p + (lane & 7) * 8;
#pragma unroll
      for (int st = 0; st < 12; st++) {
        const int n = 24 + st;
        const uint32_t lo = wlo + SLOT_OF(n) * 1024;
        mbar_wait(bar_full + SLOT_OF(n) * 8, PHASE_OF(n));
        if ((st & 3) == 0) asm volatile("bar.sync %0, 256;" ::"r"(10 + v) : "memory");
        wg_fence();
#pragma unroll
        for (int u = 0; u < 2; u++) {
#pragma unroll
          for (int j = 0; j < ((st >= 4 && (st & 2)) ? 3 : 4); j++) {
            const uint4 a = st < 4 ? B0((4 * st + j) & 15) : ((st & 2) ? B2(6 * (st & 1) + 3 * u + j) : B1(8 * (st & 1) + 4 * u + j));
            wgmma_rs_n64_tb1((st < 4 ? u == 0 : st < 8) ? aco : acc, a.x, a.y, a.z, a.w, desc<HI_W>(lo + u * 512 + j * 128), st | j);
          }
        }
        wg_commit();
        if ((st & 3) == 3 && (st < 11 || v == 0)) asm volatile("bar.arrive %0, 256;" ::"r"(11 - v) : "memory");
        if (st == 3 || st == 7) wg_wait<0>();
        else if (st > 0 && n - 1 + NSLOT < NSTAGE) wg_wait<1>();
        if (st > 0 && n - 1 + NSLOT < NSTAGE && lane == 0) mbar_arrive(bar_empty + SLOT_OF(n - 1) * 8);
        if (st == 0) {
#pragma unroll
          for (int e = 0; e < 4; e++) copy_into(B1(e), hold[e], blockIdx.y);
        }
        if (st == 3) {
          asm volatile("bar.sync %0, 160;" ::"r"(8 + v) : "memory");
          mbar_wait(bar_w, 0);
          const uint4* const hs[4] = HS4;
          settle_h1(A + 16, hs, TAG_E);
#pragma unroll
          for (int e = 3; e < 12; e++) ld_x_into(B2(e), hs[e / 3] + (8 + e % 3) * 32);
        }
        if (st == 5) {
          const uint4* const hs[4] = HS4;
          settle_h2(A, hs, TAG_E);
          const uint4* xp = XP;
#pragma unroll
          for (int jj = 0; jj < 4; jj++) ld_x_into(A[12 + jj], xp + jj * 32);
        }
        if (st == 7) {
          pin(aco);
          uint4* po = HS(0);
#pragma unroll
          for (int jj = 0; jj < 4; jj++)
            st_x(po + jj * 32, TAG_P, pack2(aco[8 * jj], aco[8 * jj + 1]), pack2(aco[8 * jj + 2], aco[8 * jj + 3]),
                 pack2(aco[8 * jj + 4], aco[8 * jj + 5]), pack2(aco[8 * jj + 6], aco[8 * jj + 7]));
          mbar_wait(bar_w, 0);
          settle4_32(A + 12, XP, TAG_E);
#pragma unroll
          for (int jj = 0; jj < 4; jj++) {
            gb[jj] = lds4f(sb + OFF_GB + (p & 1) * 256 + t * 16 + jj * 64);
            const uint32_t xx[4] = {A[12 + jj].x, A[12 + jj].y, A[12 + jj].z, A[12 + jj].w};
#pragma unroll
            for (int e = 0; e < 4; e++) { xr[2 * jj + (e >> 1)][2 * (e & 1)] = lo2f(xx[e]); xr[2 * jj + (e >> 1)][2 * (e & 1) + 1] = hi2f(xx[e]); }
          }
          keep(xr, never);
          { const uint32_t kp[4] = {sw ^ 32, sw ^ 64, sw ^ 96, sr ^ 64}; keep(kp, never); }
          keep_ptr(op, op, never);
        }
        if (st == 7) {
          const uint4* pp = PP;
#pragma unroll
          for (int jj = 0; jj < 4; jj++) ld_x_into(A[12 + jj], pp + jj * 32);
        }
      }
      mbar_wait(bar_w, 0);
      settle4_32(A + 12, PP, TAG_P);
#pragma unroll
      for (int jj = 0; jj < 4; jj++) {
        const uint32_t a[4] = {A[12 + jj].x, A[12 + jj].y, A[12 + jj].z, A[12 + jj].w};
#pragma unroll
        for (int e = 0; e < 4; e++) {
          float* q = &xr[2 * jj + (e >> 1)][2 * (e & 1)];
          q[0] = fmaf(lo2f(a[e]), (e & 2) ? gb[jj].z : gb[jj].x, q[0]);
          q[1] = fmaf(hi2f(a[e]), (e & 2) ? gb[jj].w : gb[jj].y, q[1]);
        }
      }
      wg_wait<0>();
      pin(acc);
#pragma unroll
      for (int jj = 0; jj < 4; jj++) {
        uint32_t pk[4];
#pragma unroll
        for (int e = 0; e < 4; e++)
          pk[e] = pack2(fmaf(acc[8 * jj + 2 * e], (e & 2) ? gb[jj].z : gb[jj].x, xr[2 * jj + (e >> 1)][2 * (e & 1)]),
                        fmaf(acc[8 * jj + 2 * e + 1], (e & 2) ? gb[jj].w : gb[jj].y, xr[2 * jj + (e >> 1)][2 * (e & 1) + 1]));
        stsm4(sw ^ (32 * jj), pk[0], pk[1], pk[2], pk[3]);
      }
      __syncwarp();
#pragma unroll
      for (int r = 0; r < 4; r++) {
        const uint4 o = lds4((sr ^ ((r & 1) * 64)) + r * 512);
        st_g4(op + (size_t)r * 512 * 512, o.x, o.y, o.z, o.w);
      }
    }
    if (tid == 0) st_rlx(&S.epoch[b * 8], ep0 + 1);
  }
}

typedef CUresult (*EncodeFn)(CUtensorMap*, CUtensorMapDataType, cuuint32_t, void*, const cuuint64_t*, const cuuint64_t*, const cuuint32_t*,
                             const cuuint32_t*, CUtensorMapInterleave, CUtensorMapSwizzle, CUtensorMapL2promotion, CUtensorMapFloatOOBfill);

void make_map(EncodeFn fn, CUtensorMap* m, const void* base, uint64_t inner, uint64_t outer, uint32_t b0, uint32_t b1, bool swz) {
  cuuint64_t dims[2] = {inner, outer};
  cuuint64_t strides[1] = {inner * 2};
  cuuint32_t box[2] = {b0, b1};
  cuuint32_t es[2] = {1, 1};
  fn(m, CU_TENSOR_MAP_DATA_TYPE_BFLOAT16, 2, const_cast<void*>(base), dims, strides, box, es, CU_TENSOR_MAP_INTERLEAVE_NONE,
     swz ? CU_TENSOR_MAP_SWIZZLE_128B : CU_TENSOR_MAP_SWIZZLE_NONE,
     CU_TENSOR_MAP_L2_PROMOTION_L2_128B, CU_TENSOR_MAP_FLOAT_OOB_FILL_NONE);
}

}

extern "C" void kernel_launch(void* const* d_in, const int* in_sizes, int n_in, void* d_out, int out_size) {
  static EncodeFn fn = nullptr;
  static void* scratch = nullptr;
  if (!fn) {
    cudaDriverEntryPointQueryResult qr;
    void* p = nullptr;
    cudaGetDriverEntryPoint("cuTensorMapEncodeTiled", &p, cudaEnableDefault, &qr);
    fn = (EncodeFn)p;
    cudaGetSymbolAddress(&scratch, g_s);
    cudaFuncSetAttribute(fused_kernel, cudaFuncAttributeMaxDynamicSharedMemorySize, SMEM_BYTES);
  }
  typedef const __nv_bfloat16* P;
  Maps maps;
  make_map(fn, &maps.m[0], d_in[4], 1376, 512, 64, 64, true);
  make_map(fn, &maps.m[1], d_in[5], 1376, 512, 64, 64, true);
  make_map(fn, &maps.m[2], d_in[6], 512, 1376, 64, 64, true);
  make_map(fn, &maps.m[3], d_in[1], 16 * 257, 128, 40, 128, false);
  make_map(fn, &maps.m[4], d_in[2], 16 * 257, 128, 40, 128, false);
  make_map(fn, &maps.m[5], d_in[8], 3072, 512, 16, 128, false);
  fused_kernel<<<NCTA, 384, SMEM_BYTES>>>((P)d_in[8], (P)d_in[7], (Scratch*)scratch, (P)d_in[0], (P)d_in[1], (P)d_in[2], (__nv_bfloat16*)d_out, maps);
}
```
